```python
import torch

def _softmax(x, axis=-1):
    return torch.softmax(x, dim=axis)

def _gelu(x):
    return torch.nn.functional.gelu(x, approximate='tanh')

def _silu(x):
    return torch.nn.functional.silu(x)

def _sigmoid(x):
    return torch.sigmoid(x)

def _layernorm(x, axis=-1, eps=1e-05):
    m = x.mean(dim=axis, keepdim=True)
    v = x.var(dim=axis, keepdim=True, unbiased=False)
    return (x - m) / torch.sqrt(v + eps)

def _scatter_add(tgt, idx, src, axis=0):
    return tgt.clone().index_add_(axis, idx, src)

def _segment_sum(src, seg, n):
    out = torch.zeros((n,) + src.shape[1:], dtype=src.dtype)
    return out.index_add_(0, seg, src)

def _pad(x, pw):
    flat = tuple((v for pair in reversed(pw) for v in pair))
    return torch.nn.functional.pad(x, flat)
kernel_name = 'adaLN_cond__sliding_block_cached__glu_gated_swiglu__decode'

def setup_inputs():

    _w = lambda a: (lambda t: t.to(torch.bfloat16) if t.is_floating_point() else t)(torch.as_tensor(a))

    def _A_setup():
        B, Sq, D = (2, 1, 1024)
        Hq, Hkv, Sk, Dh = (32, 4, 32768, 128)
        assert Hq % Hkv == 0, (Hq, Hkv)
        return {'x': _w((lambda *s: torch.randn(*s, dtype=torch.bfloat16) * 0.05)(B, Sq, D)), 'k_cache': _w((lambda *s: torch.randn(*s, dtype=torch.bfloat16) * 3.2)(B, Hkv, Sk, Dh)), 'v_cache': _w((lambda *s: torch.randn(*s, dtype=torch.bfloat16) * 3.2)(B, Hkv, Sk, Dh)), 'wq': _w((lambda *s: torch.randn(*s, dtype=torch.bfloat16) * 3.2)(D, Hq * Dh) * D ** (-0.5)), 'wo': _w((lambda *s: torch.randn(*s, dtype=torch.bfloat16) * 3.2)(Hq * Dh, D) * (Hq * Dh) ** (-0.5))}
    _A_in = _A_setup()

    def _B_setup():
        B, S, D, F = (2, 1, 1024, 3584)
        return {'x': _w((lambda *s: torch.randn(*s, dtype=torch.bfloat16) * 0.05)(B, S, D)), 'w1': _w((lambda *s: torch.randn(*s, dtype=torch.bfloat16) * 1.6)(D, F) * (2.0 / D) ** 0.5), 'w3': _w((lambda *s: torch.randn(*s, dtype=torch.bfloat16) * 1.6)(D, F) * (2.0 / D) ** 0.5), 'w2': _w((lambda *s: torch.randn(*s, dtype=torch.bfloat16) * 1.6)(F, D) * (2.0 / F) ** 0.5)}
    _B_in = _B_setup()
    return {'A_x': _A_in['x'], 'A_k_cache': _A_in['k_cache'], 'A_v_cache': _A_in['v_cache'], 'A_wq': _A_in['wq'], 'A_wo': _A_in['wo'], 'B_x': _B_in['x'], 'B_w1': _B_in['w1'], 'B_w3': _B_in['w3'], 'B_w2': _B_in['w2'], 'c': _w((lambda *s: torch.randn(*s, dtype=torch.bfloat16) * 0.2)(2, 1024) * 8.0), 'w_mod': _w((lambda *s: torch.randn(*s, dtype=torch.bfloat16) * 0.2)(1024, 6 * 1024) * 1024 ** (-0.5) * 8.0)}

def reference(A_x, A_k_cache, A_v_cache, A_wq, A_wo, B_x, B_w1, B_w3, B_w2, c, w_mod):

    def _A_ref(x, k_cache, v_cache, wq, wo):
        B, Sq, D = x.shape
        Hq, Dh = (32, 128)
        Hkv, Sk = (k_cache.shape[1], k_cache.shape[2])
        W = min(4096, max(256, Sk // 4))
        rep = Hq // Hkv
        q = (lambda x, *d: x.permute(*d))((x @ wq).reshape(B, Sq, Hq, Dh), 0, 2, 1, 3)
        k = (lambda x, n, axis: torch.repeat_interleave(x, n, dim=axis))(k_cache[:, :, Sk - W:, :], rep, axis=1)
        v = (lambda x, n, axis: torch.repeat_interleave(x, n, dim=axis))(v_cache[:, :, Sk - W:, :], rep, axis=1)
        scores = torch.einsum('bhqd,bhkd->bhqk', q, k) * Dh ** (-0.5)
        p = _softmax(scores, axis=-1)
        o = torch.einsum('bhqk,bhkd->bhqd', p, v)
        return (lambda x, *d: x.permute(*d))(o, 0, 2, 1, 3).reshape(B, Sq, Hq * Dh) @ wo

    def _B_ref(x, w1, w3, w2):
        gate = torch.einsum('bsd,df->bsf', x, w1)
        up = torch.einsum('bsd,df->bsf', x, w3)
        h = _silu(gate) * up
        out = torch.einsum('bsf,fd->bsd', h, w2)
        return out
    x = A_x
    mod = (_silu(c) @ w_mod).reshape(c.shape[0], 6, 1, -1)
    sa, ca, ga, sb, cb, gb = (mod[:, 0].clone(), mod[:, 1].clone(), mod[:, 2].clone(), mod[:, 3].clone(), mod[:, 4].clone(), mod[:, 5].clone())
    h = _layernorm(x, axis=-1) * (1 + ca) + sa
    x = x + ga * _A_ref(h, A_k_cache, A_v_cache, A_wq, A_wo)
    h = _layernorm(x, axis=-1) * (1 + cb) + sb
    x = x + gb * _B_ref(h, B_w1, B_w3, B_w2)
    return x
```

```cpp
#include <cuda_runtime.h>
#include <cuda_bf16.h>
#include <cuda.h>
#include <stdint.h>

namespace {

constexpr int NCTA = 128;
constexpr int NSTAGE = 12;
constexpr int STAGE_BYTES = 16384;
constexpr int NBOX = 33;
constexpr int NTHREADS = 320;
constexpr int SK = 32768, WIN = 4096;

constexpr int OFF_A = 0;
constexpr int OFF_GA = OFF_A + 16384;
constexpr int OFF_SC = OFF_GA + 16384;
constexpr int OFF_GB = OFF_SC + 16384;
constexpr int OFF_Q = OFF_GB + 16384;
constexpr int OFF_O = OFF_Q + 32768;
constexpr int OFF_ML = OFF_O + 131072;
constexpr int OFF_X = OFF_ML + 2048;
constexpr int OFF_X2 = OFF_X + 65536;
constexpr int OFF_SB = OFF_X2 + 1024;
constexpr int OFF_CB = OFF_SB + 1024;
constexpr int OFF_H = OFF_CB + 1024;
constexpr int OFF_Y = OFF_H + 28672;
constexpr int SCR_WORDS = OFF_Y + 16384;
static_assert(SCR_WORDS % (NCTA * 4) == 0, "reset slice");

__device__ __align__(1024) uint32_t g_scr[2][SCR_WORDS];
__device__ unsigned int g_epoch;

#define TS(i)
#define TSC(i)

struct Maps {
    CUtensorMap mod, wq, k, v, wo, w1, w3, w2;
};

constexpr int SM_RING = 0;
constexpr int SM_RED = NSTAGE * STAGE_BYTES;
constexpr int SM_SC = SM_RED + 8192;
constexpr int SM_H = SM_SC + 2 * 1032 * 2;
constexpr int SM_Q = SM_H + 2 * 264 * 2;
constexpr int SM_P = SM_Q + 8 * 136 * 2;
constexpr int SM_ST = SM_P + 8 * 264 * 2;
constexpr int SM_BAR = SM_ST + 1024;
constexpr int SM_TOTAL = SM_BAR + 2 * NSTAGE * 8;

constexpr unsigned SPIN_LIMIT = 1u << 22;

__device__ __forceinline__ uint32_t smem_u32(const void* p) { return (uint32_t)__cvta_generic_to_shared(p); }
__device__ __forceinline__ void mbar_init(uint32_t a, uint32_t c) {
    asm volatile("mbarrier.init.shared::cta.b64 [%0], %1;" ::"r"(a), "r"(c) : "memory");
}
__device__ __forceinline__ void mbar_expect(uint32_t a, uint32_t bytes) {
    asm volatile("mbarrier.arrive.expect_tx.shared::cta.b64 _, [%0], %1;" ::"r"(a), "r"(bytes) : "memory");
}
__device__ __forceinline__ void mbar_arrive(uint32_t a) {
    asm volatile("mbarrier.arrive.shared::cta.b64 _, [%0];" ::"r"(a) : "memory");
}
__device__ __forceinline__ void mbar_wait(uint32_t a, uint32_t parity) {
    uint32_t done;
    unsigned n = 0;
    do {
        asm volatile(
            "{\n.reg .pred p;\nmbarrier.try_wait.parity.shared::cta.b64 p, [%1], %2;\nselp.u32 %0, 1, 0, p;\n}"
            : "=r"(done) : "r"(a), "r"(parity) : "memory");
    } while (!done && ++n < SPIN_LIMIT);
}
__device__ __forceinline__ void tma2d(uint32_t dst, const CUtensorMap* m, int c0, int c1, uint32_t bar) {
    asm volatile(
        "cp.async.bulk.tensor.2d.shared::cluster.global.mbarrier::complete_tx::bytes [%0], [%1, {%3, %4}], [%2];"
        ::"r"(dst), "l"(m), "r"(bar), "r"(c0), "r"(c1) : "memory");
}
__device__ __forceinline__ void ldsm4(uint32_t (&r)[4], uint32_t a) {
    asm volatile("ldmatrix.sync.aligned.m8n8.x4.shared.b16 {%0,%1,%2,%3}, [%4];"
                 : "=r"(r[0]), "=r"(r[1]), "=r"(r[2]), "=r"(r[3]) : "r"(a) : "memory");
}
__device__ __forceinline__ void ldsm4t(uint32_t (&r)[4], uint32_t a) {
    asm volatile("ldmatrix.sync.aligned.m8n8.x4.trans.shared.b16 {%0,%1,%2,%3}, [%4];"
                 : "=r"(r[0]), "=r"(r[1]), "=r"(r[2]), "=r"(r[3]) : "r"(a) : "memory");
}
__device__ __forceinline__ void mma16816(float (&c)[4], const uint32_t (&a)[4], uint32_t b0, uint32_t b1) {
    asm volatile(
        "mma.sync.aligned.m16n8k16.row.col.f32.bf16.bf16.f32 {%0,%1,%2,%3}, {%4,%5,%6,%7}, {%8,%9}, {%0,%1,%2,%3};"
        : "+f"(c[0]), "+f"(c[1]), "+f"(c[2]), "+f"(c[3])
        : "r"(a[0]), "r"(a[1]), "r"(a[2]), "r"(a[3]), "r"(b0), "r"(b1));
}
__device__ __forceinline__ void cbar() { asm volatile("bar.sync 1, 256;" ::: "memory"); }

__device__ __forceinline__ float bfr(float x) { return __bfloat162float(__float2bfloat16_rn(x)); }
__device__ __forceinline__ uint32_t pack2(float lo, float hi) {
    __nv_bfloat162 v = __floats2bfloat162_rn(lo, hi);
    return *reinterpret_cast<uint32_t*>(&v);
}
__device__ __forceinline__ float lo16(uint32_t w) { return __uint_as_float(w << 16); }
__device__ __forceinline__ float hi16(uint32_t w) { return __uint_as_float(w & 0xffff0000u); }

__device__ __forceinline__ uint32_t enc(uint32_t b) { return b == 0xffffffffu ? 0x80000000u : ~b; }
__device__ __forceinline__ uint32_t encf(float v) { return enc(__float_as_uint(v)); }
__device__ __forceinline__ float decf(uint32_t w) { return __uint_as_float(~w); }
__device__ __forceinline__ void st1(uint32_t* p, uint32_t v) {
    asm volatile("st.relaxed.gpu.global.u32 [%0], %1;" ::"l"(p), "r"(v) : "memory");
}
__device__ __forceinline__ void st2(uint32_t* p, uint32_t a, uint32_t b) {
    asm volatile("st.relaxed.gpu.global.v2.u32 [%0], {%1,%2};" ::"l"(p), "r"(a), "r"(b) : "memory");
}
__device__ __forceinline__ uint4 ld4(const uint32_t* p) {
    uint4 v;
    asm volatile("ld.relaxed.gpu.global.v4.u32 {%0,%1,%2,%3}, [%4];"
                 : "=r"(v.x), "=r"(v.y), "=r"(v.z), "=r"(v.w) : "l"(p) : "memory");
    return v;
}
__device__ __forceinline__ uint2 ld2(const uint32_t* p) {
    uint2 v;
    asm volatile("ld.relaxed.gpu.global.v2.u32 {%0,%1}, [%2];" : "=r"(v.x), "=r"(v.y) : "l"(p) : "memory");
    return v;
}
__device__ __forceinline__ bool ok4(const uint4& v) { return v.x != 0 && v.y != 0 && v.z != 0 && v.w != 0; }
__device__ __forceinline__ bool ok2(const uint2& v) { return v.x != 0 && v.y != 0; }

template <int N>
__device__ __forceinline__ void gather4(uint4 (&v)[N], const uint32_t* p, int stride) {
#pragma unroll
    for (int i = 0; i < N; i++) v[i] = ld4(p + i * stride);
    for (unsigned n = 0; n < SPIN_LIMIT; n++) {
        bool all = true;
#pragma unroll
        for (int i = 0; i < N; i++) all = all && ok4(v[i]);
        if (all) break;
        __nanosleep(40);
#pragma unroll
        for (int i = 0; i < N; i++)
            if (!ok4(v[i])) v[i] = ld4(p + i * stride);
    }
}
template <int N>
__device__ __forceinline__ void gather2(uint2 (&v)[N], const uint32_t* p, int stride) {
#pragma unroll
    for (int i = 0; i < N; i++) v[i] = ld2(p + i * stride);
    for (unsigned n = 0; n < SPIN_LIMIT; n++) {
        bool all = true;
#pragma unroll
        for (int i = 0; i < N; i++) all = all && ok2(v[i]);
        if (all) break;
        __nanosleep(40);
#pragma unroll
        for (int i = 0; i < N; i++)
            if (!ok2(v[i])) v[i] = ld2(p + i * stride);
    }
}

struct Ring {
    uint32_t base, full, empty;
    int stage;
    uint32_t phase;
    __device__ __forceinline__ uint32_t wait() {
        mbar_wait(full + stage * 8, phase);
        return base + stage * STAGE_BYTES;
    }
    __device__ __forceinline__ void release(int lane) {
        __syncwarp();
        if (lane == 0) mbar_arrive(empty + stage * 8);
        if (++stage == NSTAGE) { stage = 0; phase ^= 1; }
    }
};

template <int NKT>
__device__ __forceinline__ void gemv_tile(float (&acc)[4], uint32_t tile_lane_addr, const __nv_bfloat16* act,
                                          bool valid, int nkt) {
    uint32_t a[NKT][4];
    uint32_t b[NKT][2];
#pragma unroll
    for (int kt = 0; kt < NKT; kt++) {
        if (kt < nkt) {
            ldsm4t(a[kt], tile_lane_addr + kt * 2048);
            b[kt][0] = valid ? *reinterpret_cast<const uint32_t*>(act + kt * 16) : 0u;
            b[kt][1] = valid ? *reinterpret_cast<const uint32_t*>(act + kt * 16 + 8) : 0u;
        }
    }
#pragma unroll
    for (int kt = 0; kt < NKT; kt++)
        if (kt < nkt) mma16816(acc, a[kt], b[kt][0], b[kt][1]);
}

__device__ __forceinline__ void red_store(float* red, int ng, int g, int kh, int mt, int lane, const float (&c)[4]) {
    if ((lane & 3) == 0) {
        float2* r = reinterpret_cast<float2*>(red + (kh * ng + g) * 128);
        r[mt * 16 + (lane >> 2)] = make_float2(c[0], c[1]);
        r[mt * 16 + 8 + (lane >> 2)] = make_float2(c[2], c[3]);
    }
}
__device__ __forceinline__ float red_get(const float* red, int ng, int g, int col, int b) {
    return red[g * 128 + col * 2 + b] + red[(ng + g) * 128 + col * 2 + b];
}

__device__ __forceinline__ void chan(float& mean, float& m2, float mean_o, float m2_o, float n) {
    float d = mean_o - mean;
    mean = 0.5f * (mean + mean_o);
    m2 = m2 + m2_o + d * d * (0.5f * n);
}

__device__ __forceinline__ void ln_stats(const float (&x)[2][4], float* st, int warp, int lane, float (&mb)[2],
                                         float (&den)[2]) {
    float mean[2], m2[2];
#pragma unroll
    for (int b = 0; b < 2; b++) {
        float mu = 0.25f * ((x[b][0] + x[b][1]) + (x[b][2] + x[b][3]));
        float s = 0.f;
#pragma unroll
        for (int i = 0; i < 4; i++) s += (x[b][i] - mu) * (x[b][i] - mu);
        float n = 4.f;
#pragma unroll
        for (int o = 1; o < 32; o <<= 1) {
            float mo = __shfl_xor_sync(0xffffffffu, mu, o);
            float so = __shfl_xor_sync(0xffffffffu, s, o);
            chan(mu, s, mo, so, n);
            n *= 2.f;
        }
        mean[b] = mu;
        m2[b] = s;
    }
    if (lane == 0) *reinterpret_cast<float4*>(st + warp * 4) = make_float4(mean[0], m2[0], mean[1], m2[1]);
    cbar();
    float4 t[8];
#pragma unroll
    for (int w = 0; w < 8; w++) t[w] = *reinterpret_cast<const float4*>(st + w * 4);
#pragma unroll
    for (int s = 1, n = 128; s < 8; s <<= 1, n <<= 1) {
#pragma unroll
        for (int w = 0; w < 8; w += 2 * s) {
            chan(t[w].x, t[w].y, t[w + s].x, t[w + s].y, (float)n);
            chan(t[w].z, t[w].w, t[w + s].z, t[w + s].w, (float)n);
        }
    }
    mb[0] = bfr(t[0].x);
    mb[1] = bfr(t[0].z);
    den[0] = bfr(sqrtf(bfr(bfr(t[0].y * (1.f / 1024.f)) + 1e-5f)));
    den[1] = bfr(sqrtf(bfr(bfr(t[0].w * (1.f / 1024.f)) + 1e-5f)));
}

__device__ __forceinline__ float silu_f(float x) { return x / (1.f + expf(-x)); }

__global__ void __launch_bounds__(NTHREADS, 1)
fused_kernel(const __grid_constant__ Maps maps, const __nv_bfloat16* __restrict__ x_in,
             const __nv_bfloat16* __restrict__ c_in, __nv_bfloat16* __restrict__ out) {
    extern __shared__ __align__(1024) unsigned char smem[];
    const int tid = threadIdx.x, warp = tid >> 5, lane = tid & 31;
    const int cta = blockIdx.x;
    const uint32_t sbase = smem_u32(smem);

    if (tid == 256) {
        for (int i = 0; i < NSTAGE; i++) {
            mbar_init(sbase + SM_BAR + i * 8, 1);
            mbar_init(sbase + SM_BAR + (NSTAGE + i) * 8, 8);
        }
        asm volatile("fence.mbarrier_init.release.cluster;" ::: "memory");
    }
    TSC(0);
    __syncthreads();

    if (warp == 8) {
        if (lane == 0) {
            int stage = 0;
            uint32_t phase = 1;
            const int kvrow = (cta >> 4) * SK + (SK - WIN) + (cta & 15) * 256;
#pragma unroll 1
            for (int it = 0; it < NBOX; it++) {
                const uint32_t dst = sbase + SM_RING + stage * STAGE_BYTES;
                const uint32_t bar = sbase + SM_BAR + stage * 8;
                if (it >= NSTAGE) mbar_wait(sbase + SM_BAR + (NSTAGE + stage) * 8, phase);
                mbar_expect(bar, it >= 29 ? 14336 : 16384);
                if (it < 2) {
                    tma2d(dst, &maps.mod, (cta & 31) * 64, (cta >> 5) * 256 + it * 128, bar);
                } else if (it == 2) {
                    tma2d(dst, &maps.mod, 2048 + (cta & 15) * 64, (cta >> 4) * 128, bar);
                } else if (it < 7) {
                    int j = it - 3;
                    tma2d(dst, &maps.wq, (cta & 31) * 128 + (j & 1) * 64, (cta >> 5) * 256 + (j >> 1) * 128, bar);
                } else if (it < 9) {
                    tma2d(dst, &maps.mod, 3072 + (cta & 31) * 64, (cta >> 5) * 256 + (it - 7) * 128, bar);
                } else if (it < 13) {
                    int j = it - 9;
                    tma2d(dst, &maps.k, (j & 1) * 64, kvrow + (j >> 1) * 128, bar);
                } else if (it < 17) {
                    int j = it - 13;
                    tma2d(dst, &maps.v, 0, kvrow + j * 64, bar);
                    tma2d(dst + 8192, &maps.v, 64, kvrow + j * 64, bar);
                } else if (it == 17) {
                    tma2d(dst, &maps.mod, 5120 + (cta & 15) * 64, (cta >> 4) * 128, bar);
                } else if (it < 22) {
                    tma2d(dst, &maps.wo, (cta & 3) * 256 + (it - 18) * 64, (cta >> 2) * 128, bar);
                } else if (it < 29) {
                    int g = cta * 7 + (it - 22);
                    int col = g >> 3, rb = g & 7;
                    if (col < 56) tma2d(dst, &maps.w1, col * 64, rb * 128, bar);
                    else tma2d(dst, &maps.w3, (col - 56) * 64, rb * 128, bar);
                } else {
                    tma2d(dst, &maps.w2, (cta & 15) * 64, (cta >> 4) * 448 + (it - 29) * 112, bar);
                }
                if (++stage == NSTAGE) { stage = 0; phase ^= 1; }
            }
        }
        return;
    }

    const unsigned epoch = *reinterpret_cast<volatile unsigned int*>(&g_epoch);
    uint32_t* scr = g_scr[epoch & 1];

    if (warp == 9) {
        const int b = (lane >> 1) & 1, c4 = (lane & 1) * 4;
        float xv[4];
        {
            uint2 t = *reinterpret_cast<const uint2*>(x_in + b * 1024 + cta * 8 + c4);
            xv[0] = lo16(t.x); xv[1] = hi16(t.x); xv[2] = lo16(t.y); xv[3] = hi16(t.y);
        }
        auto red8 = [&](float (&v)[4]) {
#pragma unroll
            for (int o = 4; o < 32; o <<= 1)
#pragma unroll
                for (int i = 0; i < 4; i++) v[i] += __shfl_xor_sync(0xffffffffu, v[i], o);
        };
        float ga[4], gb[4], x2[4];
        {
            uint4 v[1];
            gather4<1>(v, scr + OFF_GA + cta * 128 + lane * 4, 0);
            ga[0] = decf(v[0].x); ga[1] = decf(v[0].y); ga[2] = decf(v[0].z); ga[3] = decf(v[0].w);
            __syncwarp();
            red8(ga);
#pragma unroll
            for (int i = 0; i < 4; i++) ga[i] = bfr(ga[i]);
        }
        {
            uint4 v[1];
            gather4<1>(v, scr + OFF_SC + cta * 128 + lane * 4, 0);
            float s[4] = {decf(v[0].x), decf(v[0].y), decf(v[0].z), decf(v[0].w)};
            __syncwarp();
#pragma unroll
            for (int o = 4; o < 16; o <<= 1)
#pragma unroll
                for (int i = 0; i < 4; i++) s[i] += __shfl_xor_sync(0xffffffffu, s[i], o);
            const bool isc = lane >= 16;
#pragma unroll
            for (int i = 0; i < 4; i++) {
                s[i] = bfr(s[i]);
                if (isc) s[i] = bfr(1.f + s[i]);
            }
            float o[4];
#pragma unroll
            for (int i = 0; i < 4; i++) o[i] = __shfl_down_sync(0xffffffffu, s[i], 2);
            if ((lane & 14) == 0) {
                uint32_t* p = scr + (isc ? OFF_CB : OFF_SB) + cta * 8 + c4;
                st2(p, enc(pack2(s[0], o[0])), enc(pack2(s[1], o[1])));
                st2(p + 2, enc(pack2(s[2], o[2])), enc(pack2(s[3], o[3])));
            }
        }
        {
            uint4 v[1];
            gather4<1>(v, scr + OFF_GB + cta * 128 + lane * 4, 0);
            gb[0] = decf(v[0].x); gb[1] = decf(v[0].y); gb[2] = decf(v[0].z); gb[3] = decf(v[0].w);
            __syncwarp();
            red8(gb);
#pragma unroll
            for (int i = 0; i < 4; i++) gb[i] = bfr(gb[i]);
        }
        TS(20);
        {
            uint4 v[4];
            gather4<4>(v, scr + OFF_X + cta * 512 + lane * 4, 128);
            float s[4];
            s[0] = (decf(v[0].x) + decf(v[1].x)) + (decf(v[2].x) + decf(v[3].x));
            s[1] = (decf(v[0].y) + decf(v[1].y)) + (decf(v[2].y) + decf(v[3].y));
            s[2] = (decf(v[0].z) + decf(v[1].z)) + (decf(v[2].z) + decf(v[3].z));
            s[3] = (decf(v[0].w) + decf(v[1].w)) + (decf(v[2].w) + decf(v[3].w));
            __syncwarp();
            red8(s);
            float o[4];
#pragma unroll
            for (int i = 0; i < 4; i++) {
                x2[i] = bfr(xv[i] + bfr(ga[i] * bfr(s[i])));
                o[i] = __shfl_down_sync(0xffffffffu, x2[i], 2);
            }
            if (lane < 2) {
                uint32_t* p = scr + OFF_X2 + cta * 8 + c4;
                st2(p, enc(pack2(x2[0], o[0])), enc(pack2(x2[1], o[1])));
                st2(p + 2, enc(pack2(x2[2], o[2])), enc(pack2(x2[3], o[3])));
            }
        }
        TS(21);
        {
            uint4 v[1];
            gather4<1>(v, scr + OFF_Y + cta * 128 + lane * 4, 0);
            float s[4] = {decf(v[0].x), decf(v[0].y), decf(v[0].z), decf(v[0].w)};
            __syncwarp();
            red8(s);
            if (lane < 4) {
                float r[4];
#pragma unroll
                for (int i = 0; i < 4; i++) r[i] = x2[i] + bfr(gb[i] * bfr(s[i]));
                uint2 o = make_uint2(pack2(r[0], r[1]), pack2(r[2], r[3]));
                *reinterpret_cast<uint2*>(out + b * 1024 + cta * 8 + c4) = o;
            }
        }
        TS(22);
        if (cta == 0 && lane == 0) *reinterpret_cast<volatile unsigned int*>(&g_epoch) = epoch + 1;
        return;
    }

    Ring ring{sbase + SM_RING, sbase + SM_BAR, sbase + SM_BAR + NSTAGE * 8, 0, 0u};
    float* red0 = reinterpret_cast<float*>(smem + SM_RED);
    float* red1 = reinterpret_cast<float*>(smem + SM_RED + 4096);
    __nv_bfloat16* sc_s = reinterpret_cast<__nv_bfloat16*>(smem + SM_SC);
    __nv_bfloat16* h_s = reinterpret_cast<__nv_bfloat16*>(smem + SM_H);
    __nv_bfloat16* q_s = reinterpret_cast<__nv_bfloat16*>(smem + SM_Q);
    __nv_bfloat16* p_s = reinterpret_cast<__nv_bfloat16*>(smem + SM_P);
    float* st_s = reinterpret_cast<float*>(smem + SM_ST);

    const int mt = warp & 3, kh = warp >> 2;
    const int lj = lane >> 3, l7 = lane & 7;
    const uint32_t toff = (uint32_t)(kh * 8192 + ((lj >> 1) * 8 + l7) * 128 + (((mt * 2 + (lj & 1)) ^ l7) << 4));
    const int bn = lane >> 2, bk = (lane & 3) * 2;
    const bool bvalid = bn < 2;

    float mb1[2], den1[2];
    {
        float xv[2][4];
#pragma unroll
        for (int b = 0; b < 2; b++) {
            uint2 t = *reinterpret_cast<const uint2*>(x_in + b * 1024 + tid * 4);
            xv[b][0] = lo16(t.x); xv[b][1] = hi16(t.x); xv[b][2] = lo16(t.y); xv[b][3] = hi16(t.y);
            uint2 cc = *reinterpret_cast<const uint2*>(c_in + b * 1024 + tid * 4);
            uint2 o = make_uint2(pack2(silu_f(lo16(cc.x)), silu_f(hi16(cc.x))), pack2(silu_f(lo16(cc.y)), silu_f(hi16(cc.y))));
            *reinterpret_cast<uint2*>(sc_s + b * 1032 + tid * 4) = o;
        }
        uint4* z = reinterpret_cast<uint4*>(g_scr[(epoch & 1) ^ 1]) + cta * (SCR_WORDS / NCTA / 4);
        for (int i = tid; i < SCR_WORDS / NCTA / 4; i += 256) z[i] = make_uint4(0, 0, 0, 0);
        ln_stats(xv, st_s, warp, lane, mb1, den1);
    }
    TSC(1);

    {
        float acc[4] = {0, 0, 0, 0};
        const __nv_bfloat16* act = sc_s + bn * 1032 + (cta >> 5) * 256 + kh * 64 + bk;
#pragma unroll
        for (int j = 0; j < 2; j++) {
            uint32_t t = ring.wait();
            gemv_tile<4>(acc, t + toff, act + j * 128, bvalid, 4);
            ring.release(lane);
        }
        red_store(red0, 1, 0, kh, mt, lane, acc);
        cbar();
        if (tid < 128) {
            int b = tid >> 6, col = tid & 63;
            st1(scr + OFF_A + ((cta >> 5) * 2 + b) * 2048 + (cta & 31) * 64 + col, encf(red_get(red0, 1, 0, col, b)));
        }
    }
    TSC(2);
    {
        float acc[4] = {0, 0, 0, 0};
        uint32_t t = ring.wait();
        gemv_tile<4>(acc, t + toff, sc_s + bn * 1032 + (cta >> 4) * 128 + kh * 64 + bk, bvalid, 4);
        ring.release(lane);
        red_store(red1, 1, 0, kh, mt, lane, acc);
        cbar();
        if (tid < 128) {
            int cb = tid >> 4, b = (tid >> 3) & 1, c8 = tid & 7;
            st1(scr + OFF_GA + ((cta & 15) * 8 + cb) * 128 + (cta >> 4) * 16 + b * 8 + c8,
                encf(red_get(red1, 1, 0, cb * 8 + c8, b)));
        }
    }
    TSC(3);
    {
        const int b = tid >> 7, k0 = (cta >> 5) * 256 + (tid & 127) * 2;
        uint32_t xw = *reinterpret_cast<const uint32_t*>(x_in + b * 1024 + k0);
        uint2 v[8];
        {
            const uint32_t* p = scr + OFF_A + b * 2048 + k0;
            uint2 (&va)[4] = *reinterpret_cast<uint2(*)[4]>(&v[0]);
            uint2 (&vc)[4] = *reinterpret_cast<uint2(*)[4]>(&v[4]);
#pragma unroll
            for (int i = 0; i < 4; i++) vc[i] = ld2(p + 1024 + i * 4096);
            gather2<4>(va, p, 4096);
            for (unsigned n = 0; n < SPIN_LIMIT; n++) {
                bool all = true;
#pragma unroll
                for (int i = 0; i < 4; i++) all = all && ok2(vc[i]);
                if (all) break;
#pragma unroll
                for (int i = 0; i < 4; i++)
                    if (!ok2(vc[i])) vc[i] = ld2(p + 1024 + i * 4096);
            }
        }
        float sa0 = bfr((decf(v[0].x) + decf(v[1].x)) + (decf(v[2].x) + decf(v[3].x)));
        float sa1 = bfr((decf(v[0].y) + decf(v[1].y)) + (decf(v[2].y) + decf(v[3].y)));
        float ca0 = bfr((decf(v[4].x) + decf(v[5].x)) + (decf(v[6].x) + decf(v[7].x)));
        float ca1 = bfr((decf(v[4].y) + decf(v[5].y)) + (decf(v[6].y) + decf(v[7].y)));
        const float m = b ? mb1[1] : mb1[0], dn = b ? den1[1] : den1[0];
        float l0 = bfr(bfr(lo16(xw) - m) / dn), l1 = bfr(bfr(hi16(xw) - m) / dn);
        float h0 = bfr(l0 * bfr(1.f + ca0)) + sa0, h1 = bfr(l1 * bfr(1.f + ca1)) + sa1;
        *reinterpret_cast<uint32_t*>(h_s + b * 264 + (tid & 127) * 2) = pack2(h0, h1);
        cbar();
    }
    TSC(4);
    {
        float acc[2][4] = {{0, 0, 0, 0}, {0, 0, 0, 0}};
        const __nv_bfloat16* act = h_s + bn * 264 + kh * 64 + bk;
#pragma unroll
        for (int j = 0; j < 4; j++) {
            uint32_t t = ring.wait();
            gemv_tile<4>(acc[j & 1], t + toff, act + (j >> 1) * 128, bvalid, 4);
            ring.release(lane);
        }
        red_store(red0, 2, 0, kh, mt, lane, acc[0]);
        red_store(red0, 2, 1, kh, mt, lane, acc[1]);
        cbar();
        int b = tid >> 7, col = tid & 127;
        st1(scr + OFF_Q + (b * 4 + (cta >> 5)) * 4096 + (cta & 31) * 128 + col,
            encf(red_get(red0, 2, col >> 6, col & 63, b)));
    }
    TSC(5);
    {
        float acc[4] = {0, 0, 0, 0};
        const __nv_bfloat16* act = sc_s + bn * 1032 + (cta >> 5) * 256 + kh * 64 + bk;
#pragma unroll
        for (int j = 0; j < 2; j++) {
            uint32_t t = ring.wait();
            gemv_tile<4>(acc, t + toff, act + j * 128, bvalid, 4);
            ring.release(lane);
        }
        red_store(red1, 1, 0, kh, mt, lane, acc);
        cbar();
        if (tid < 128) {
            int cb = tid >> 4, b = (tid >> 3) & 1, c8 = tid & 7;
            int which = (cta >> 4) & 1;
            st1(scr + OFF_SC + ((cta & 15) * 8 + cb) * 128 + which * 64 + (cta >> 5) * 16 + b * 8 + c8,
                encf(red_get(red1, 1, 0, cb * 8 + c8, b)));
        }
    }
    TSC(6);
    const int ab = cta >> 6, ahkv = (cta >> 4) & 3, asplit = cta & 15;
    {
        uint4 v[4];
        gather4<4>(v, scr + OFF_Q + ab * 16384 + ahkv * 1024 + tid * 4, 4096);
        float q0 = (decf(v[0].x) + decf(v[1].x)) + (decf(v[2].x) + decf(v[3].x));
        float q1 = (decf(v[0].y) + decf(v[1].y)) + (decf(v[2].y) + decf(v[3].y));
        float q2 = (decf(v[0].z) + decf(v[1].z)) + (decf(v[2].z) + decf(v[3].z));
        float q3 = (decf(v[0].w) + decf(v[1].w)) + (decf(v[2].w) + decf(v[3].w));
        *reinterpret_cast<uint2*>(q_s + warp * 136 + lane * 4) = make_uint2(pack2(q0, q1), pack2(q2, q3));
        cbar();
    }
    TSC(7);
    {
        float s[2][4] = {{0, 0, 0, 0}, {0, 0, 0, 0}};
        const __nv_bfloat16* qf = q_s + bn * 136 + bk;
        const uint32_t koff = (uint32_t)((warp * 16 + (lj & 1) * 8 + l7) * 128);
#pragma unroll
        for (int j = 0; j < 4; j++) {
            uint32_t t = ring.wait();
            uint32_t a[4][4];
#pragma unroll
            for (int kt = 0; kt < 4; kt++) ldsm4(a[kt], t + koff + (((kt * 2 + (lj >> 1)) ^ l7) << 4));
#pragma unroll
            for (int kt = 0; kt < 4; kt++) {
                uint32_t b0 = *reinterpret_cast<const uint32_t*>(qf + (j & 1) * 64 + kt * 16);
                uint32_t b1 = *reinterpret_cast<const uint32_t*>(qf + (j & 1) * 64 + kt * 16 + 8);
                mma16816(s[j >> 1], a[kt], b0, b1);
            }
            ring.release(lane);
        }
        const float scale = 0.08838834764831845f;
#pragma unroll
        for (int g = 0; g < 2; g++)
#pragma unroll
            for (int i = 0; i < 4; i++) s[g][i] = bfr(bfr(s[g][i]) * scale);
        float m0 = fmaxf(fmaxf(s[0][0], s[0][2]), fmaxf(s[1][0], s[1][2]));
        float m1 = fmaxf(fmaxf(s[0][1], s[0][3]), fmaxf(s[1][1], s[1][3]));
#pragma unroll
        for (int o = 4; o < 32; o <<= 1) {
            m0 = fmaxf(m0, __shfl_xor_sync(0xffffffffu, m0, o));
            m1 = fmaxf(m1, __shfl_xor_sync(0xffffffffu, m1, o));
        }
        if (lane < 4) *reinterpret_cast<float2*>(st_s + 64 + warp * 8 + lane * 2) = make_float2(m0, m1);
        cbar();
#pragma unroll
        for (int w = 0; w < 8; w++) {
            float2 t = *reinterpret_cast<const float2*>(st_s + 64 + w * 8 + bk);
            m0 = fmaxf(m0, t.x);
            m1 = fmaxf(m1, t.y);
        }
        float l0 = 0.f, l1 = 0.f;
#pragma unroll
        for (int g = 0; g < 2; g++) {
            const int key = g * 128 + warp * 16 + bn;
            float p0 = __expf(s[g][0] - m0), p1 = __expf(s[g][1] - m1);
            float p2 = __expf(s[g][2] - m0), p3 = __expf(s[g][3] - m1);
            l0 += p0 + p2;
            l1 += p1 + p3;
            p_s[bk * 264 + key] = __float2bfloat16_rn(p0);
            p_s[(bk + 1) * 264 + key] = __float2bfloat16_rn(p1);
            p_s[bk * 264 + key + 8] = __float2bfloat16_rn(p2);
            p_s[(bk + 1) * 264 + key + 8] = __float2bfloat16_rn(p3);
        }
#pragma unroll
        for (int o = 4; o < 32; o <<= 1) {
            l0 += __shfl_xor_sync(0xffffffffu, l0, o);
            l1 += __shfl_xor_sync(0xffffffffu, l1, o);
        }
        if (lane < 4) *reinterpret_cast<float2*>(st_s + 128 + warp * 8 + lane * 2) = make_float2(l0, l1);
        cbar();
        if (tid < 4) {
            float t0 = 0.f, t1 = 0.f;
#pragma unroll
            for (int w = 0; w < 8; w++) {
                float2 t = *reinterpret_cast<const float2*>(st_s + 128 + w * 8 + bk);
                t0 += t.x;
                t1 += t.y;
            }
            uint32_t* p = scr + OFF_ML + ((ab * 32 + ahkv * 8 + bk) * 16 + asplit) * 2;
            st2(p, encf(m0), encf(t0));
            st2(p + 32, encf(m1), encf(t1));
        }
        TSC(8);
        float o[4] = {0, 0, 0, 0};
        const __nv_bfloat16* pf = p_s + bn * 264 + bk;
#pragma unroll
        for (int j = 0; j < 4; j++) {
            uint32_t t = ring.wait();
            gemv_tile<4>(o, t + toff, pf + j * 64, true, 4);
            ring.release(lane);
        }
        uint32_t* p = scr + OFF_O + ((ab * 32 + ahkv * 8 + bk) * 16 + asplit) * 128 + warp * 16 + bn;
        st1(p, encf(o[0]));
        st1(p + 2048, encf(o[1]));
        st1(p + 8, encf(o[2]));
        st1(p + 2048 + 8, encf(o[3]));
    }
    TSC(9);
    {
        float acc[4] = {0, 0, 0, 0};
        uint32_t t = ring.wait();
        gemv_tile<4>(acc, t + toff, sc_s + bn * 1032 + (cta >> 4) * 128 + kh * 64 + bk, bvalid, 4);
        ring.release(lane);
        red_store(red0, 1, 0, kh, mt, lane, acc);
        cbar();
        if (tid < 128) {
            int cb = tid >> 4, b = (tid >> 3) & 1, c8 = tid & 7;
            st1(scr + OFF_GB + ((cta & 15) * 8 + cb) * 128 + (cta >> 4) * 16 + b * 8 + c8,
                encf(red_get(red0, 1, 0, cb * 8 + c8, b)));
        }
    }
    TSC(10);
    {
        const int h = cta >> 2, b = warp >> 2, g = warp & 3;
        uint4 v[4];
        const uint32_t* po = scr + OFF_O + ((b * 32 + h) * 16 + g * 4) * 128 + lane * 4;
#pragma unroll
        for (int i = 0; i < 4; i++) v[i] = ld4(po + i * 128);
        uint2 ml[1];
        gather2<1>(ml, scr + OFF_ML + ((b * 32 + h) * 16 + (lane & 15)) * 2, 0);
        __syncwarp();
        float m = decf(ml[0].x), l = decf(ml[0].y);
        float M = m;
#pragma unroll
        for (int o = 1; o < 16; o <<= 1) M = fmaxf(M, __shfl_xor_sync(0xffffffffu, M, o));
        float w = __expf(m - M);
        float L = w * l;
#pragma unroll
        for (int o = 1; o < 16; o <<= 1) L += __shfl_xor_sync(0xffffffffu, L, o);
        w = w / L;
        for (unsigned n = 0; n < SPIN_LIMIT; n++) {
            bool all = true;
#pragma unroll
            for (int i = 0; i < 4; i++) all = all && ok4(v[i]);
            if (all) break;
            __nanosleep(40);
#pragma unroll
            for (int i = 0; i < 4; i++)
                if (!ok4(v[i])) v[i] = ld4(po + i * 128);
        }
        __syncwarp();
        float4 r = make_float4(0, 0, 0, 0);
#pragma unroll
        for (int i = 0; i < 4; i++) {
            float a = __shfl_sync(0xffffffffu, w, g * 4 + i);
            r.x += a * decf(v[i].x);
            r.y += a * decf(v[i].y);
            r.z += a * decf(v[i].z);
            r.w += a * decf(v[i].w);
        }
        *reinterpret_cast<float4*>(red1 + warp * 128 + lane * 4) = r;
        cbar();
        {
            const int bb = tid >> 7, d = tid & 127;
            const float* rr = red1 + bb * 512 + d;
            h_s[bb * 136 + d] = __float2bfloat16_rn((rr[0] + rr[128]) + (rr[256] + rr[384]));
        }
        cbar();
    }
    TSC(11);
    {
        float acc[4][4];
        const __nv_bfloat16* act = h_s + bn * 136 + kh * 64 + bk;
#pragma unroll
        for (int j = 0; j < 4; j++) {
            acc[j][0] = acc[j][1] = acc[j][2] = acc[j][3] = 0.f;
            uint32_t t = ring.wait();
            gemv_tile<4>(acc[j], t + toff, act, bvalid, 4);
            ring.release(lane);
            red_store(red0, 4, j, kh, mt, lane, acc[j]);
        }
        cbar();
        const int cb = tid >> 3, b = (tid >> 2) & 1, c2 = (tid & 3) * 2;
        const int col = cb * 8 + c2;
        st2(scr + OFF_X + ((cta & 3) * 32 + cb) * 512 + (cta >> 2) * 16 + b * 8 + c2,
            encf(red_get(red0, 4, col >> 6, col & 63, b)), encf(red_get(red0, 4, col >> 6, (col & 63) + 1, b)));
    }
    TSC(12);
    {
        uint4 sb[2];
        gather4<2>(sb, scr + OFF_SB + tid * 4, 1024);
        uint4 v[1];
        gather4<1>(v, scr + OFF_X2 + tid * 4, 0);
        uint32_t xw[4] = {~v[0].x, ~v[0].y, ~v[0].z, ~v[0].w};
        uint32_t sw[4] = {~sb[0].x, ~sb[0].y, ~sb[0].z, ~sb[0].w};
        uint32_t cw[4] = {~sb[1].x, ~sb[1].y, ~sb[1].z, ~sb[1].w};
        float xv[2][4];
#pragma unroll
        for (int i = 0; i < 4; i++) { xv[0][i] = lo16(xw[i]); xv[1][i] = hi16(xw[i]); }
        __syncwarp();
        float mb[2], den[2];
        ln_stats(xv, st_s, warp, lane, mb, den);
        float h[2][4];
#pragma unroll
        for (int i = 0; i < 4; i++) {
            h[0][i] = bfr(bfr(bfr(xv[0][i] - mb[0]) / den[0]) * lo16(cw[i])) + lo16(sw[i]);
            h[1][i] = bfr(bfr(bfr(xv[1][i] - mb[1]) / den[1]) * hi16(cw[i])) + hi16(sw[i]);
        }
        *reinterpret_cast<uint2*>(sc_s + tid * 4) = make_uint2(pack2(h[0][0], h[0][1]), pack2(h[0][2], h[0][3]));
        *reinterpret_cast<uint2*>(sc_s + 1032 + tid * 4) = make_uint2(pack2(h[1][0], h[1][1]), pack2(h[1][2], h[1][3]));
        cbar();
    }
    TSC(13);
    {
        float acc[2][4] = {{0, 0, 0, 0}, {0, 0, 0, 0}};
        const int g0 = cta * 7, c0 = g0 >> 3;
        const __nv_bfloat16* act = sc_s + bn * 1032 + kh * 64 + bk;
#pragma unroll
        for (int j = 0; j < 7; j++) {
            const int g = g0 + j;
            uint32_t t = ring.wait();
            if ((g >> 3) == c0) gemv_tile<4>(acc[0], t + toff, act + (g & 7) * 128, bvalid, 4);
            else gemv_tile<4>(acc[1], t + toff, act + (g & 7) * 128, bvalid, 4);
            ring.release(lane);
        }
        red_store(red1, 2, 0, kh, mt, lane, acc[0]);
        red_store(red1, 2, 1, kh, mt, lane, acc[1]);
        cbar();
        const int gi = tid >> 7, b = (tid >> 6) & 1, col = tid & 63;
        const int c = c0 + gi;
        if (gi == 0 || ((g0 + 6) >> 3) != c0) {
            const int part = (cta == (c * 8) / 7) ? 0 : 1;
            st1(scr + OFF_H + (part * 112 + c) * 128 + b * 64 + col, encf(red_get(red1, 2, gi, col, b)));
        }
    }
    TSC(14);
    {
        if (tid < 224) {
            const int cj = tid >> 5, b = (tid >> 4) & 1, q4 = (tid & 15) * 4;
            uint4 v[4];
            gather4<4>(v, scr + OFF_H + ((cta >> 4) * 7 + cj) * 128 + b * 64 + q4, 56 * 128);
            float g[4] = {decf(v[0].x) + decf(v[2].x), decf(v[0].y) + decf(v[2].y), decf(v[0].z) + decf(v[2].z),
                          decf(v[0].w) + decf(v[2].w)};
            float u[4] = {decf(v[1].x) + decf(v[3].x), decf(v[1].y) + decf(v[3].y), decf(v[1].z) + decf(v[3].z),
                          decf(v[1].w) + decf(v[3].w)};
            float r[4];
#pragma unroll
            for (int i = 0; i < 4; i++) r[i] = bfr(silu_f(bfr(g[i]))) * bfr(u[i]);
            *reinterpret_cast<uint2*>(p_s + b * 456 + cj * 64 + q4) = make_uint2(pack2(r[0], r[1]), pack2(r[2], r[3]));
        }
        cbar();
    }
    TSC(15);
    {
        float acc[4] = {0, 0, 0, 0};
        const __nv_bfloat16* act = p_s + bn * 456 + kh * 64 + bk;
#pragma unroll
        for (int j = 0; j < 4; j++) {
            uint32_t t = ring.wait();
            gemv_tile<4>(acc, t + toff, act + j * 112, bvalid, kh == 0 ? 4 : 3);
            ring.release(lane);
        }
        red_store(red0, 1, 0, kh, mt, lane, acc);
        cbar();
        if (tid < 128) {
            int cb = tid >> 4, b = (tid >> 3) & 1, c8 = tid & 7;
            st1(scr + OFF_Y + ((cta & 15) * 8 + cb) * 128 + (cta >> 4) * 16 + b * 8 + c8,
                encf(red_get(red0, 1, 0, cb * 8 + c8, b)));
        }
    }
    TSC(16);
}

typedef CUresult (*EncodeFn)(CUtensorMap*, CUtensorMapDataType, cuuint32_t, void*, const cuuint64_t*,
                             const cuuint64_t*, const cuuint32_t*, const cuuint32_t*, CUtensorMapInterleave,
                             CUtensorMapSwizzle, CUtensorMapL2promotion, CUtensorMapFloatOOBfill);

void make_map(EncodeFn fn, CUtensorMap* m, const void* base, uint64_t rows, uint64_t cols, uint32_t box_rows) {
    cuuint64_t gd[2] = {cols, rows};
    cuuint64_t gs[1] = {cols * 2};
    cuuint32_t bx[2] = {64, box_rows};
    cuuint32_t es[2] = {1, 1};
    fn(m, CU_TENSOR_MAP_DATA_TYPE_BFLOAT16, 2, const_cast<void*>(base), gd, gs, bx, es,
       CU_TENSOR_MAP_INTERLEAVE_NONE, CU_TENSOR_MAP_SWIZZLE_128B, CU_TENSOR_MAP_L2_PROMOTION_L2_256B,
       CU_TENSOR_MAP_FLOAT_OOB_FILL_NONE);
}

}

extern "C" void kernel_launch(void* const* d_in, const int* in_sizes, int n_in, void* d_out, int out_size) {
    (void)in_sizes; (void)n_in; (void)out_size;
    static EncodeFn enc_fn = nullptr;
    if (!enc_fn) {
        cudaDriverEntryPointQueryResult qr;
        void* fn = nullptr;
        cudaGetDriverEntryPoint("cuTensorMapEncodeTiled", &fn, cudaEnableDefault, &qr);
        enc_fn = (EncodeFn)fn;
        cudaFuncSetAttribute(fused_kernel, cudaFuncAttributeMaxDynamicSharedMemorySize, SM_TOTAL);
    }
    Maps maps;
    make_map(enc_fn, &maps.mod, d_in[10], 1024, 6144, 128);
    make_map(enc_fn, &maps.wq, d_in[3], 1024, 4096, 128);
    make_map(enc_fn, &maps.k, d_in[1], (uint64_t)8 * SK, 128, 128);
    make_map(enc_fn, &maps.v, d_in[2], (uint64_t)8 * SK, 128, 64);
    make_map(enc_fn, &maps.wo, d_in[4], 4096, 1024, 128);
    make_map(enc_fn, &maps.w1, d_in[6], 1024, 3584, 128);
    make_map(enc_fn, &maps.w3, d_in[7], 1024, 3584, 128);
    make_map(enc_fn, &maps.w2, d_in[8], 3584, 1024, 112);
    fused_kernel<<<NCTA, NTHREADS, SM_TOTAL>>>(maps, (const __nv_bfloat16*)d_in[0], (const __nv_bfloat16*)d_in[9],
                                               (__nv_bfloat16*)d_out);
}
```

```cpp
#include <cuda_runtime.h>
#include <cuda_bf16.h>
#include <cuda.h>
#include <stdint.h>

namespace {

constexpr int NCTA = 128;
constexpr int NSTAGE = 12;
constexpr int STAGE_BYTES = 16384;
constexpr int NBOX = 33;
#define INFLIGHT 3
#define PACE_NS 630
#define PACE_STAGGER 315
#define PACE_SLACK 0
#define PACE_END 99
#define PACE_B0 1
constexpr int NTHREADS = 320;
constexpr int SK = 32768, WIN = 4096;

constexpr int R_A = 0;
constexpr int R_Q = 128;
constexpr int R_M0 = 384;
constexpr int R_O = 512;
constexpr int R_X = 1536;
constexpr int R_H = 2048;
constexpr int R_Y = 2304;
constexpr int R_M1 = 2432;
constexpr int R_GB = 2560;
constexpr int R_M2 = 2688;
constexpr int R_ML = 2816;
constexpr int R_CNT = 2848;
constexpr int RSZ = 2880;
constexpr int C_O = 0, C_X = 4, C_X2 = 8, C_H = 16;
#define TMPF 2
#define EARLYPF 0
#define ZMODE 1
#define HINTMASK 31
#define NFIRST 2
#define XMODE 0
#define YMODE 0
#define X2MODE 0
#define GATE_NUM 4
constexpr int T_A = 0, T_Q = 2, T_M = 6, T_K = 9, T_V = 13, T_WO = 17, T_E = 21, T_GB = 28, T_F = 29;
constexpr int G_X2 = NCTA * RSZ;
constexpr int G_SC = G_X2 + 2048;

__device__ __align__(1024) uint32_t g_scr[G_SC + 4096];
__device__ unsigned int g_epoch;

#define TSP(i, cond)
#define TS(i)
#define TSC(i)
#define UNLIKELY(x) __builtin_expect(!!(x), 0)
#define PIN(p) asm volatile("" : "+l"(p))
#define PIN32(p) asm volatile("" : "+r"(p))

struct Maps {
    CUtensorMap mod, wq, k, v, wo, w1, w3, w2;
};

constexpr int SM_RING = 0;
constexpr int SM_SC = NSTAGE * STAGE_BYTES;
constexpr int SM_H2 = SM_SC + 4096;
constexpr int SM_H = SM_H2 + 4096;
constexpr int SM_HH = SM_H + 1024;
constexpr int SM_Q = SM_HH + 2048;
constexpr int SM_P = SM_Q + 8 * 272;
constexpr int SM_ST = SM_P + 8 * 528;
constexpr int SM_TAB = SM_ST + 1024;
constexpr int SM_BAR = SM_TAB + 1024;
constexpr int SM_TOTAL = SM_BAR + 2 * NSTAGE * 8;

constexpr unsigned SPIN_LIMIT = 1u << 22;

#define PRED(n) "{\n.reg .pred p;\nsetp.ne.u32 p, %" #n ", 0;\n@p "

__device__ __forceinline__ uint32_t smem_u32(const void* p) { return (uint32_t)__cvta_generic_to_shared(p); }
__device__ __forceinline__ void mbar_init(uint32_t a, uint32_t c) {
    asm volatile("mbarrier.init.shared::cta.b64 [%0], %1;" ::"r"(a), "r"(c) : "memory");
}
__device__ __forceinline__ void mbar_expect(uint32_t a, uint32_t bytes) {
    asm volatile("mbarrier.arrive.expect_tx.shared::cta.b64 _, [%0], %1;" ::"r"(a), "r"(bytes) : "memory");
}
__device__ __forceinline__ void mbar_arrive_p(uint32_t a, uint32_t pred) {
    asm volatile(PRED(1) "mbarrier.arrive.shared::cta.b64 _, [%0];\n}" ::"r"(a), "r"(pred) : "memory");
}
__device__ __forceinline__ uint32_t mbar_try(uint32_t a, uint32_t parity) {
    uint32_t done;
    asm volatile(
        "{\n.reg .pred p;\nmbarrier.try_wait.parity.shared::cta.b64 p, [%1], %2;\nselp.u32 %0, 1, 0, p;\n}"
        : "=r"(done) : "r"(a), "r"(parity) : "memory");
    return done;
}
__device__ __forceinline__ uint32_t mbar_test_p(uint32_t a, uint32_t parity, uint32_t pred) {
    uint32_t done;
    asm volatile(
        "{\n.reg .pred p, q;\nsetp.ne.u32 p, %3, 0;\nsetp.ne.u32 q, %3, %3;\n"
        "@p mbarrier.test_wait.parity.shared::cta.b64 q, [%1], %2;\nselp.u32 %0, 1, 0, q;\n}"
        : "=r"(done) : "r"(a), "r"(parity), "r"(pred) : "memory");
    return done;
}
__device__ __forceinline__ void mbar_wait(uint32_t a, uint32_t parity) {
    unsigned n = 0;
    while (!mbar_try(a, parity) && ++n < SPIN_LIMIT) {}
}
__device__ __noinline__ void mbar_wait_slow(uint32_t a, uint32_t parity, uint32_t live) {
    if (live) mbar_wait(a, parity);
}
__device__ __forceinline__ void tma3d(uint32_t dst, const void* m, int c0, int c1, uint32_t bar, uint64_t pol) {
    asm volatile(
        "cp.async.bulk.tensor.3d.shared::cluster.global.mbarrier::complete_tx::bytes.L2::cache_hint"
        " [%0], [%1, {%3, %4, %5}], [%2], %6;"
        ::"r"(dst), "l"(m), "r"(bar), "r"(c0), "r"(c1), "r"(0), "l"(pol) : "memory");
}
__device__ __forceinline__ void ldsm4(uint32_t (&r)[4], uint32_t a) {
    asm volatile("ldmatrix.sync.aligned.m8n8.x4.shared.b16 {%0,%1,%2,%3}, [%4];"
                 : "=r"(r[0]), "=r"(r[1]), "=r"(r[2]), "=r"(r[3]) : "r"(a) : "memory");
}
__device__ __forceinline__ void ldsm4t(uint32_t (&r)[4], uint32_t a) {
    asm volatile("ldmatrix.sync.aligned.m8n8.x4.trans.shared.b16 {%0,%1,%2,%3}, [%4];"
                 : "=r"(r[0]), "=r"(r[1]), "=r"(r[2]), "=r"(r[3]) : "r"(a) : "memory");
}
__device__ __forceinline__ void lds128(uint32_t (&r)[4], uint32_t a) {
    asm volatile("ld.shared.v4.u32 {%0,%1,%2,%3}, [%4];"
                 : "=r"(r[0]), "=r"(r[1]), "=r"(r[2]), "=r"(r[3]) : "r"(a) : "memory");
}
__device__ __forceinline__ void mma16816(float (&c)[4], const uint32_t (&a)[4], uint32_t b0, uint32_t b1) {
    asm volatile(
        "mma.sync.aligned.m16n8k16.row.col.f32.bf16.bf16.f32 {%0,%1,%2,%3}, {%4,%5,%6,%7}, {%8,%9}, {%0,%1,%2,%3};"
        : "+f"(c[0]), "+f"(c[1]), "+f"(c[2]), "+f"(c[3])
        : "r"(a[0]), "r"(a[1]), "r"(a[2]), "r"(a[3]), "r"(b0), "r"(b1));
}
__device__ __forceinline__ void mma16816_z(float (&c)[4], const uint32_t (&a)[4], uint32_t b0, uint32_t b1) {
    asm volatile(
        "mma.sync.aligned.m16n8k16.row.col.f32.bf16.bf16.f32 {%0,%1,%2,%3}, {%4,%5,%6,%7}, {%8,%9}, {%10,%10,%10,%10};"
        : "=f"(c[0]), "=f"(c[1]), "=f"(c[2]), "=f"(c[3])
        : "r"(a[0]), "r"(a[1]), "r"(a[2]), "r"(a[3]), "r"(b0), "r"(b1), "f"(0.f));
}
template <int ID, int N> __device__ __forceinline__ void bar_sync(uint32_t pred) {
    asm volatile(PRED(2) "bar.sync %0, %1;\n}" ::"n"(ID), "n"(N), "r"(pred) : "memory");
}
template <int ID, int N> __device__ __forceinline__ void bar_arrive(uint32_t pred) {
    asm volatile(PRED(2) "bar.arrive %0, %1;\n}" ::"n"(ID), "n"(N), "r"(pred) : "memory");
}
constexpr int BAR_ALPHA = 2, BAR_XGO = 3, BAR_MGO = 4, BAR_ZERO = 5;

__device__ __forceinline__ uint32_t pack2(float lo, float hi) {
    uint32_t r;
    asm("cvt.rn.bf16x2.f32 %0, %1, %2;" : "=r"(r) : "f"(hi), "f"(lo));
    return r;
}
__device__ __forceinline__ float bfr(float x) { return __uint_as_float(pack2(0.f, x)); }
__device__ __forceinline__ float lo16(uint32_t w) { return __uint_as_float(w << 16); }
__device__ __forceinline__ float hi16(uint32_t w) { return __uint_as_float(w & 0xffff0000u); }

__device__ __forceinline__ uint32_t encf(float v, uint32_t tag) { return (__float_as_uint(v) & ~3u) | tag; }
__device__ __forceinline__ float decf(uint32_t w) { return __uint_as_float(w & ~3u); }
__device__ __forceinline__ void st2(uint32_t* p, uint32_t a, uint32_t b, uint32_t pred) {
    asm volatile(PRED(3) "st.relaxed.gpu.global.v2.u32 [%0], {%1,%2};\n}" ::"l"(p), "r"(a), "r"(b), "r"(pred) : "memory");
}
__device__ __forceinline__ void st4(uint32_t* p, uint32_t a, uint32_t b, uint32_t c, uint32_t d, uint32_t pred) {
    asm volatile(PRED(5) "st.relaxed.gpu.global.v4.u32 [%0], {%1,%2,%3,%4};\n}"
                 ::"l"(p), "r"(a), "r"(b), "r"(c), "r"(d), "r"(pred) : "memory");
}
__device__ __forceinline__ void st64x2(uint32_t* p, uint64_t a, uint64_t b, uint32_t pred) {
    asm volatile(PRED(3) "st.relaxed.gpu.global.v2.u64 [%0], {%1,%2};\n}" ::"l"(p), "l"(a), "l"(b), "r"(pred) : "memory");
}
__device__ __forceinline__ void sts16_p(uint32_t a, uint32_t v, uint32_t pred) {
    asm volatile(PRED(2) "st.shared.u16 [%0], %1;\n}" ::"r"(a), "h"((uint16_t)v), "r"(pred) : "memory");
}
__device__ __forceinline__ void sts32_p(uint32_t a, uint32_t v, uint32_t pred) {
    asm volatile(PRED(2) "st.shared.u32 [%0], %1;\n}" ::"r"(a), "r"(v), "r"(pred) : "memory");
}
__device__ __forceinline__ void sts64_p(uint32_t a, uint32_t x, uint32_t y, uint32_t pred) {
    asm volatile(PRED(3) "st.shared.v2.u32 [%0], {%1,%2};\n}" ::"r"(a), "r"(x), "r"(y), "r"(pred) : "memory");
}
__device__ __forceinline__ void sts128_p(uint32_t a, float x, float y, float z, float w, uint32_t pred) {
    asm volatile(PRED(5) "st.shared.v4.f32 [%0], {%1,%2,%3,%4};\n}"
                 ::"r"(a), "f"(x), "f"(y), "f"(z), "f"(w), "r"(pred) : "memory");
}
__device__ __forceinline__ void ldx(uint4& v, const uint32_t* p) {
    asm volatile("ld.relaxed.gpu.global.v4.u32 {%0,%1,%2,%3}, [%4];"
                 : "=r"(v.x), "=r"(v.y), "=r"(v.z), "=r"(v.w) : "l"(p) : "memory");
}
__device__ __forceinline__ void ldx(uint2& v, const uint32_t* p) {
    asm volatile("ld.relaxed.gpu.global.v2.u32 {%0,%1}, [%2];" : "=r"(v.x), "=r"(v.y) : "l"(p) : "memory");
}
__device__ __forceinline__ void ldx(uint32_t& v, const uint32_t* p) {
    asm volatile("ld.relaxed.gpu.global.u32 %0, [%1];" : "=r"(v) : "l"(p) : "memory");
}
__device__ __forceinline__ void ldx(ulonglong2& v, const uint32_t* p) {
    asm volatile("ld.relaxed.gpu.global.v2.u64 {%0,%1}, [%2];" : "=l"(v.x), "=l"(v.y) : "l"(p) : "memory");
}
__device__ __forceinline__ uint32_t andw(const uint4& v) { return v.x & v.y & v.z & v.w; }
__device__ __forceinline__ uint32_t andw(const uint2& v) { return v.x & v.y; }
__device__ __forceinline__ uint32_t andw(const uint32_t& v) { return v; }
__device__ __forceinline__ uint32_t andw(const ulonglong2& v) { return (uint32_t)v.x & (uint32_t)v.y; }

template <int N, typename T, typename F>
__device__ __forceinline__ void gatherf(T (&v)[N], uint32_t tag, F addr) {
    uint32_t all = tag;
#pragma unroll
    for (int i = 0; i < N; i++) ldx(v[i], addr(i));
#pragma unroll
    for (int i = 0; i < N; i++) all &= andw(v[i]);
    if (UNLIKELY(!__all_sync(0xffffffffu, all))) {
        for (unsigned n = 0; n < SPIN_LIMIT; n++) {
            uint32_t bad = 0;
#pragma unroll
            for (int i = 0; i < N; i++) bad |= (andw(v[i]) & tag) ? 0u : 1u << i;
            bad = __reduce_or_sync(0xffffffffu, bad);
            if (!bad) break;
#pragma unroll
            for (int i = 0; i < N; i++)
                if (bad & (1u << i)) ldx(v[i], addr(i));
        }
    }
}
template <int STRIDE, int N, typename T>
__device__ __forceinline__ void poll(T (&v)[N], uint32_t tag, const uint32_t* p) {
    unsigned n = 0;
    bool ok;
    do {
        uint32_t all = tag;
#pragma unroll
        for (int i = 0; i < N; i++) ldx(v[i], p + i * STRIDE);
#pragma unroll
        for (int i = 0; i < N; i++) all &= andw(v[i]);
        ok = __all_sync(0xffffffffu, all);
    } while (!ok && ++n < SPIN_LIMIT);
}
template <int STRIDE, int N, typename T>
__device__ __forceinline__ void gather(T (&v)[N], uint32_t tag, const uint32_t* p) {
    gatherf<N>(v, tag, [&](int i) { return p + i * STRIDE; });
}
__device__ __forceinline__ void cnt_wait(const uint32_t* p, uint32_t target) {
    uint32_t v;
    unsigned n = 0;
    do { ldx(v, p); } while (v < target && ++n < SPIN_LIMIT);
}
__device__ __forceinline__ void cnt_add(uint32_t* p, uint32_t pred) {
    asm volatile(PRED(1) "red.relaxed.gpu.global.add.u32 [%0], 1;\n}" ::"l"(p), "r"(pred) : "memory");
}
__device__ __forceinline__ void cta_arrive(uint32_t scnt, uint32_t* gcnt, uint32_t lane0) {
    uint32_t old = 0;
    asm volatile(PRED(2) "atom.shared.add.u32 %0, [%1], 1;\n}" : "+r"(old) : "r"(scnt), "r"(lane0) : "memory");
    cnt_add(gcnt, old == 7);
}

__device__ __forceinline__ int frag_off(int b, int k) {
    return (k >> 5) * 128 + b * 64 + ((k >> 1) & 3) * 16 + ((k >> 3) & 1) * 8 + ((k >> 4) & 1) * 4;
}

struct Acc {
    float c[8][4];
    __device__ __forceinline__ float s0() const { return (c[0][0] + c[1][2]) + (c[2][0] + c[3][2]); }
    __device__ __forceinline__ float s1() const { return (c[0][1] + c[1][3]) + (c[2][1] + c[3][3]); }
    __device__ __forceinline__ void pick(int r, float& v0, float& v1) const {
        const bool o = r & 1, h = r & 2;
        const float e0 = h ? (o ? c[6][0] : c[4][0]) : (o ? c[2][0] : c[0][0]);
        const float e1 = h ? (o ? c[6][1] : c[4][1]) : (o ? c[2][1] : c[0][1]);
        const float d0 = h ? (o ? c[7][2] : c[5][2]) : (o ? c[3][2] : c[1][2]);
        const float d1 = h ? (o ? c[7][3] : c[5][3]) : (o ? c[3][3] : c[1][3]);
        v0 = e0 + d0;
        v1 = e1 + d1;
    }
};

template <typename F>
__device__ __forceinline__ void ln_stats(const float (&x)[2][4], uint32_t st_addr, const float* st, int warp,
                                         uint32_t lane0, uint32_t live, float (&mb)[2], float (&den)[2], F after_barrier) {
    float r[4], piv[2];
#pragma unroll
    for (int b = 0; b < 2; b++) {
        piv[b] = __shfl_sync(0xffffffffu, x[b][0], 0);
        float d0 = x[b][0] - piv[b], d1 = x[b][1] - piv[b], d2 = x[b][2] - piv[b], d3 = x[b][3] - piv[b];
        r[b * 2] = (d0 + d1) + (d2 + d3);
        r[b * 2 + 1] = (d0 * d0 + d1 * d1) + (d2 * d2 + d3 * d3);
    }
#pragma unroll
    for (int o = 1; o < 32; o <<= 1)
#pragma unroll
        for (int i = 0; i < 4; i++) r[i] += __shfl_xor_sync(0xffffffffu, r[i], o);
    sts128_p(st_addr + warp * 16, piv[0] + r[0] * (1.f / 128.f), r[1] - r[0] * r[0] * (1.f / 128.f),
             piv[1] + r[2] * (1.f / 128.f), r[3] - r[2] * r[2] * (1.f / 128.f), lane0);
    bar_sync<1, 256>(live);
    float4 t[8];
#pragma unroll
    for (int w = 0; w < 8; w++) t[w] = *reinterpret_cast<const float4*>(st + w * 4);
    after_barrier();
    const float m0 = (((t[0].x + t[1].x) + (t[2].x + t[3].x)) + ((t[4].x + t[5].x) + (t[6].x + t[7].x))) * 0.125f;
    const float m1 = (((t[0].z + t[1].z) + (t[2].z + t[3].z)) + ((t[4].z + t[5].z) + (t[6].z + t[7].z))) * 0.125f;
#pragma unroll
    for (int w = 0; w < 8; w++) {
        t[w].y += 128.f * (t[w].x - m0) * (t[w].x - m0);
        t[w].w += 128.f * (t[w].z - m1) * (t[w].z - m1);
    }
    const float v0 = (((t[0].y + t[1].y) + (t[2].y + t[3].y)) + ((t[4].y + t[5].y) + (t[6].y + t[7].y))) * (1.f / 1024.f);
    const float v1 = (((t[0].w + t[1].w) + (t[2].w + t[3].w)) + ((t[4].w + t[5].w) + (t[6].w + t[7].w))) * (1.f / 1024.f);
    mb[0] = bfr(m0);
    mb[1] = bfr(m1);
    float s0, s1;
    asm("sqrt.approx.ftz.f32 %0, %1;" : "=f"(s0) : "f"(bfr(bfr(fmaxf(v0, 0.f)) + 1e-5f)));
    asm("sqrt.approx.ftz.f32 %0, %1;" : "=f"(s1) : "f"(bfr(bfr(fmaxf(v1, 0.f)) + 1e-5f)));
    den[0] = bfr(s0);
    den[1] = bfr(s1);
}

__device__ __forceinline__ float silu_f(float x) { return __fdividef(x, 1.f + __expf(-x)); }

__global__ void __launch_bounds__(NTHREADS, 1)
fused_kernel(const __grid_constant__ Maps maps, const __nv_bfloat16* __restrict__ x_in,
             const __nv_bfloat16* __restrict__ c_in, __nv_bfloat16* __restrict__ out,
             const __nv_bfloat16* __restrict__ wmod, const __nv_bfloat16* __restrict__ wq) {
    extern __shared__ __align__(1024) unsigned char smem[];
    const int tid = threadIdx.x, warp = tid >> 5, lane = tid & 31;
    const int cta = blockIdx.x;
    const uint32_t sbase = smem_u32(smem);
    uint32_t* const scr = g_scr;
    uint32_t* const mine = g_scr + cta * RSZ;

    if (warp == 8) {
        uint32_t tnext;
        asm volatile("mov.u32 %0, %%globaltimer_lo;" : "=r"(tnext));
        uint64_t pol;
        asm volatile("createpolicy.fractional.L2::evict_first.b64 %0, 1.0;" : "=l"(pol));
        uint64_t poln;
        asm volatile("createpolicy.fractional.L2::evict_normal.b64 %0, 1.0;" : "=l"(poln));
        if (lane < NSTAGE) {
            mbar_init(sbase + SM_BAR + lane * 8, 1);
            mbar_init(sbase + SM_BAR + (NSTAGE + lane) * 8, 8);
            asm volatile("fence.mbarrier_init.release.cluster;" ::: "memory");
        }
        __syncwarp();
        if (lane == 0) {
#pragma unroll
            for (int i = 0; i < NFIRST; i++) {
                mbar_expect(sbase + SM_BAR + i * 8, 16384);
                if (i < 2) tma3d(sbase + SM_RING + i * STAGE_BYTES, &maps.mod, (cta & 31) * 64, (cta >> 5) * 256 + i * 128,
                                 sbase + SM_BAR + i * 8, (HINTMASK & 1) ? pol : poln);
                else tma3d(sbase + SM_RING + i * STAGE_BYTES, &maps.wq, (cta & 31) * 128 + (i & 1) * 64, (cta >> 5) * 256,
                           sbase + SM_BAR + i * 8, (HINTMASK & 2) ? pol : poln);
            }
        }
        __syncwarp();
        bar_arrive<0, NTHREADS - 32>(1);
        {
            const int it = lane + 1;
            const int kvrow = (cta >> 4) * SK + (SK - WIN) + (cta & 15) * 256;
            int m, c0, c1;
            if (it < T_Q) {
                m = 0; c0 = (cta & 31) * 64; c1 = (cta >> 5) * 256 + it * 128;
            } else if (it < T_M) {
                int j = it - T_Q;
                m = 1; c0 = (cta & 31) * 128 + (j & 1) * 64; c1 = (cta >> 5) * 256 + (j >> 1) * 128;
            } else if (it == T_GB) {
                m = 0; c0 = 5120 + (cta & 15) * 64; c1 = (cta >> 4) * 128;
            } else if (it < T_K) {
                const int idx = cta + 128 * (it - T_M);
                m = 0; c0 = 2048 + (idx % 48) * 64; c1 = (idx / 48) * 128;
            } else if (it < T_V) {
                m = 2; c0 = 0; c1 = kvrow + (it - T_K) * 64;
            } else if (it < T_WO) {
                int j = it - T_V;
                m = 3; c0 = (j & 1) * 64; c1 = kvrow + (j >> 1) * 128;
            } else if (it < T_E) {
                m = 4; c0 = (cta & 3) * 256 + (it - T_WO) * 64; c1 = (cta >> 2) * 128;
            } else if (it < T_GB) {
                int g = cta * 7 + (it - T_E);
                int col = g >> 3;
                m = col < 56 ? 5 : 6;
                c0 = (col < 56 ? col : col - 56) * 64; c1 = (g & 7) * 128;
            } else {
                m = 7; c0 = (cta & 15) * 64; c1 = (cta >> 4) * 448 + (it - T_F) * 112;
            }
            *reinterpret_cast<int4*>(smem + SM_TAB + it * 16) = make_int4(m * 128, c0, c1, it >= T_F ? 14336 : 16384);
        }
        __syncwarp();
        if (lane == 0) {
            int stage = NFIRST;
            uint32_t phase = 1;
            tnext += ((cta * 37) & 127) * PACE_NS / 128 - PACE_STAGGER;
#pragma unroll 1
            for (int it = NFIRST; it < NBOX; it++) {
                const int4 e = *reinterpret_cast<const int4*>(smem + SM_TAB + it * 16);
                const uint32_t bar = sbase + SM_BAR + stage * 8;
                const int dd = INFLIGHT;
                if (it >= dd) {
                    const int ps = stage >= dd ? stage - dd : stage - dd + NSTAGE;
                    mbar_wait(sbase + SM_BAR + ps * 8, stage >= dd ? phase ^ 1 : phase);
                }
                if (it >= NSTAGE) mbar_wait(bar + NSTAGE * 8, phase);
                if (PACE_NS > 0 && it >= PACE_B0 && it < PACE_END) {
                    tnext += PACE_NS;
                    uint32_t now;
                    unsigned n = 0;
                    do {
                        asm volatile("mov.u32 %0, %%globaltimer_lo;" : "=r"(now));
                    } while ((int)(now - tnext) < 0 && ++n < SPIN_LIMIT);
                    if ((int)(now - PACE_SLACK - tnext) > 0) tnext = now - PACE_SLACK;
                }
                if (it < 6 + NFIRST) asm volatile("prefetch.tensormap [%0];" ::"l"(reinterpret_cast<const char*>(&maps) + (it + 2 - NFIRST) * 128) : "memory");
                mbar_expect(bar, e.w);
                tma3d(sbase + SM_RING + stage * STAGE_BYTES, reinterpret_cast<const char*>(&maps) + e.x, e.y, e.z, bar, ((HINTMASK >> (e.x >> 7)) & 1) ? pol : poln);
                if (++stage == NSTAGE) { stage = 0; phase ^= 1; }
            }
        }
        return;
    }

    const unsigned epoch = *reinterpret_cast<volatile unsigned int*>(&g_epoch);

    if (warp == 9) {
        const int b = (lane >> 1) & 1, c4 = (lane & 1) * 4;
        const uint2 xr = *reinterpret_cast<const uint2*>(x_in + b * 1024 + cta * 8 + c4);
        st4(mine + R_A + lane * 4, 0, 0, 0, 0, 1);
        st4(mine + R_M0 + lane * 4, 0, 0, 0, 0, 1);
        for (int i = R_Y / 4 + lane; i < RSZ / 4; i += 32) st4(mine + i * 4, 0, 0, 0, 0, 1);
        uint32_t* px2 = scr + G_X2 + b * 1024 + cta * 8 + c4;
        uint32_t* const psc = scr + G_SC + (b * 1024 + cta * 8 + c4) * 2 + ((lane >> 2) & 1) * 4;
        st4(px2, 0, 0, 0, 0, lane < 4);
        st4(psc, 0, 0, 0, 0, lane < 8);
        asm volatile("fence.acq_rel.gpu;" ::: "memory");
        __syncwarp();
        bar_arrive<BAR_ZERO, 288>(1);
        const uint32_t tag = 1 + (epoch & 1);
        const int coff = b * 64 + (cta & 7) * 8 + c4;
        const float xv[4] = {lo16(xr.x), hi16(xr.x), lo16(xr.y), hi16(xr.y)};
        auto red8 = [&](float (&v)[4]) {
#pragma unroll
            for (int o = 4; o < 32; o <<= 1)
#pragma unroll
                for (int i = 0; i < 4; i++) v[i] += __shfl_xor_sync(0xffffffffu, v[i], o);
        };
        {
            constexpr uint32_t live = 1;
            auto gentle = [&](const uint32_t* p) -> uint4 {
                uint4 v;
                for (unsigned n = 0; n < SPIN_LIMIT; n++) {
                    __nanosleep(300);
                    ldx(v, p);
                    if (__all_sync(0xffffffffu, andw(v) & tag)) break;
                }
                return v;
            };
            float ga[4], gb[4], x2[4];
            bar_sync<BAR_MGO, 288>(live);
            {
                float md[3][4];
#pragma unroll
                for (int w = 0; w < 3; w++) {
                    const int idx = (lane >> 2) * 48 + w * 16 + (cta >> 3);
                    const int j = idx >> 7;
                    const uint4 v = gentle(scr + (idx & 127) * RSZ + (j == 0 ? R_M0 : j == 1 ? R_M1 : R_M2) + coff);
                    md[w][0] = decf(v.x); md[w][1] = decf(v.y); md[w][2] = decf(v.z); md[w][3] = decf(v.w);
                    red8(md[w]);
                }
                uint64_t pk[4];
#pragma unroll
                for (int i = 0; i < 4; i++) {
                    ga[i] = bfr(md[0][i]);
                    pk[i] = ((uint64_t)pack2(md[1][i], 1.f + bfr(md[2][i])) << 32) | tag;
                }
                st64x2(psc, lane < 4 ? pk[0] : pk[2], lane < 4 ? pk[1] : pk[3], lane < 8);
            }
            TS(19);
            {
                const int h = cta >> 2;
                const uint32_t* p = scr + ((lane >> 4) * 64 + (h >> 3) * 16 + (lane & 15)) * RSZ + R_ML + (h & 7) * 2;
                uint2 ml;
                bar_sync<BAR_MGO, 288>(live);
                for (unsigned n = 0; n < SPIN_LIMIT; n++) {
                    __nanosleep(300);
                    ldx(ml, p);
                    if (__all_sync(0xffffffffu, ml.x & ml.y & tag)) break;
                }
                float m = decf(ml.x), l = decf(ml.y);
                float M = m;
#pragma unroll
                for (int o = 1; o < 16; o <<= 1) M = fmaxf(M, __shfl_xor_sync(0xffffffffu, M, o));
                float w = __expf(m - M);
                float L = w * l;
#pragma unroll
                for (int o = 1; o < 16; o <<= 1) L += __shfl_xor_sync(0xffffffffu, L, o);
                sts32_p(sbase + SM_ST + (192 + lane) * 4, __float_as_uint(__fdividef(w, L)), live);
                __syncwarp();
                bar_arrive<BAR_ALPHA, 288>(live);
            }
            {
                const uint32_t* p = mine + R_X + lane * 4;
                uint32_t* pc = scr + C_X2 * RSZ + R_CNT;
                PIN(p); PIN(px2); PIN(pc);
                cnt_wait(scr + (C_X + (cta >> 5)) * RSZ + R_CNT, 256);
                uint4 v[4];
                poll<128>(v, tag, p);
                float s[4];
                s[0] = (decf(v[0].x) + decf(v[1].x)) + (decf(v[2].x) + decf(v[3].x));
                s[1] = (decf(v[0].y) + decf(v[1].y)) + (decf(v[2].y) + decf(v[3].y));
                s[2] = (decf(v[0].z) + decf(v[1].z)) + (decf(v[2].z) + decf(v[3].z));
                s[3] = (decf(v[0].w) + decf(v[1].w)) + (decf(v[2].w) + decf(v[3].w));
                red8(s);
#pragma unroll
                for (int i = 0; i < 4; i++) x2[i] = bfr(xv[i] + bfr(ga[i] * bfr(s[i])));
                st4(px2, __float_as_uint(x2[0]) | tag, __float_as_uint(x2[1]) | tag, __float_as_uint(x2[2]) | tag,
                    __float_as_uint(x2[3]) | tag, live && lane < 4);
                cnt_add(pc, live && lane == 0);
            }
            TS(21);
            {
                const uint32_t* p = mine + R_Y + lane * 4;
                uint32_t* po = reinterpret_cast<uint32_t*>(out + b * 1024 + cta * 8 + c4);
                PIN(p); PIN(po);
                bar_sync<BAR_XGO, 288>(live);
                uint4 v[2];
                poll<R_GB - R_Y>(v, tag, p);
                float s[4] = {decf(v[0].x), decf(v[0].y), decf(v[0].z), decf(v[0].w)};
                gb[0] = decf(v[1].x); gb[1] = decf(v[1].y); gb[2] = decf(v[1].z); gb[3] = decf(v[1].w);
                red8(s);
                red8(gb);
                float r[4];
#pragma unroll
                for (int i = 0; i < 4; i++) r[i] = x2[i] + bfr(bfr(gb[i]) * bfr(s[i]));
                st2(po, pack2(r[0], r[1]), pack2(r[2], r[3]), live && lane < 4);
            }
            TS(22);
        }
        if (cta == 0 && lane == 0) *reinterpret_cast<volatile unsigned int*>(&g_epoch) = epoch + 1;
        return;
    }

    TSP(0, tid == 0);
    const uint2 xr0 = *reinterpret_cast<const uint2*>(x_in + tid * 4);
    const uint2 xr1 = *reinterpret_cast<const uint2*>(x_in + 1024 + tid * 4);
    const uint2 cr0 = *reinterpret_cast<const uint2*>(c_in + tid * 4);
    const uint2 cr1 = *reinterpret_cast<const uint2*>(c_in + 1024 + tid * 4);
    const uint32_t xw = *reinterpret_cast<const uint32_t*>(x_in + (tid >> 7) * 1024 + (cta >> 5) * 256 + (tid & 127) * 2);

    const float* st_s = reinterpret_cast<const float*>(smem + SM_ST);
    const int lj = lane >> 3, l7 = lane & 7;
    const int g8 = lane >> 2, q2 = (lane & 3) * 2;
    uint32_t taddr = sbase + SM_RING + lane * 128 + ((warp ^ l7) << 4);
    uint32_t aaddr = sbase + lane * 16;
    const uint32_t fullb = sbase + SM_BAR, emptyb = sbase + SM_BAR + NSTAGE * 8;
    const uint32_t lt8 = lane < 8;
    uint32_t* pub = mine + (g8 & 1) * 64 + warp * 8 + q2;
    PIN32(taddr); PIN32(aaddr); PIN(pub);
    uint32_t* px = scr + ((cta & 3) * 32 + warp) * RSZ + R_X + (cta >> 2) * 16 + (g8 & 1) * 8 + q2;
    uint32_t* py = scr + ((cta & 15) * 8 + warp) * RSZ + R_Y + (cta >> 4) * 16 + (g8 & 1) * 8 + q2;
    const int ljp = ((lj & 1) << 1) | (lj >> 1);

    uint32_t af[8][4];
    uint32_t wf[2][4][4];
    Acc acc, acc2;
    float ln0 = 0.f, ln1 = 0.f;

    {
    constexpr uint32_t live = 1, secs = 0xff;
    const uint32_t lo8 = live && lt8, lane0 = live && lane == 0;
    const uint32_t tag = live ? 1 + (epoch & 1) : 3;
    uint32_t rdy = 0;

    auto cbar = [&]() { bar_sync<1, 256>(live); };
    auto load_af = [&](int i, int off) { lds128(af[i], aaddr + off); };
    auto load_af8 = [&](int i, uint32_t addr) {
#pragma unroll
        for (int c = 0; c < 4; c++) ldsm4(af[i + c], addr + c * 64);
    };
    auto tscan = [&](int it0, int n) {
        const int it = it0 + lane;
        const uint32_t m = __ballot_sync(0xffffffffu, mbar_test_p(fullb + (it % NSTAGE) * 8, (it / NSTAGE) & 1, live && lane < n));
        rdy = (m << (it0 & 31)) | (m >> ((32 - it0) & 31));
    };
    auto tfetch = [&](int it) {
        if (UNLIKELY(!((rdy >> (it & 31)) & 1))) mbar_wait_slow(fullb + (it % NSTAGE) * 8, (it / NSTAGE) & 1, live);
        if (it >= T_K && it < T_V) {
            const uint32_t ka = sbase + SM_RING + (it % NSTAGE) * STAGE_BYTES + (warp * 8 + l7) * 128;
#pragma unroll
            for (int c = 0; c < 4; c++) ldsm4(wf[it & 1][c], ka + (c >> 1) * 8192 + ((((c & 1) * 4 + lj) ^ l7) << 4));
        } else {
#pragma unroll
            for (int c = 0; c < 4; c++) ldsm4t(wf[it & 1][c], taddr + (it % NSTAGE) * STAGE_BYTES + c * 4096);
        }
    };
    auto tmma = [&](Acc& ac, int ai, int it, bool first) {
        const bool rows8 = it >= T_K && it < T_WO;
#pragma unroll
        for (int kt = 0; kt < 8; kt++) {
            const uint32_t b0 = wf[it & 1][kt >> 1][(kt & 1) * 2], b1 = wf[it & 1][kt >> 1][(kt & 1) * 2 + 1];
            if (it >= T_F && kt == 7) {
                if (first) ac.c[7][2] = ac.c[7][3] = 0.f;
            } else if (rows8) {
                if (first && kt < 4) mma16816_z(ac.c[kt], af[ai + (kt >> 1)], b0, b1);
                else mma16816(ac.c[kt & 3], af[ai + (kt >> 1)], b0, b1);
            } else {
                if (first) mma16816_z(ac.c[kt], af[ai], b0, b1);
                else mma16816(ac.c[kt], af[ai], b0, b1);
            }
        }
        if (it + NSTAGE < NBOX) {
            __syncwarp();
            mbar_arrive_p(emptyb + (it % NSTAGE) * 8, lane0);
        }
    };
    auto publish2 = [&](float v0, float v1, uint32_t* dst) {
        v0 += __shfl_xor_sync(0xffffffffu, v0, 8);
        v1 += __shfl_xor_sync(0xffffffffu, v1, 8);
        v0 += __shfl_xor_sync(0xffffffffu, v0, 16);
        v1 += __shfl_xor_sync(0xffffffffu, v1, 16);
        st2(dst, encf(v0, tag), encf(v1, tag), lo8);
    };
    auto publish = [&](const Acc& ac, uint32_t* dst) {
        float v0, v1;
        ac.pick(lj, v0, v1);
        publish2(v0, v1, dst);
    };

    if (secs & 1) {
        const uint32_t o = sbase + SM_SC + frag_off(0, tid * 4);
        sts32_p(o, pack2(silu_f(lo16(cr0.x)), silu_f(hi16(cr0.x))), live);
        sts32_p(o + 16, pack2(silu_f(lo16(cr0.y)), silu_f(hi16(cr0.y))), live);
        sts32_p(o + 64, pack2(silu_f(lo16(cr1.x)), silu_f(hi16(cr1.x))), live);
        sts32_p(o + 80, pack2(silu_f(lo16(cr1.y)), silu_f(hi16(cr1.y))), live);
        sts32_p(sbase + SM_ST + 960 + (tid & 3) * 4, 0, live && tid < 4);
        bar_sync<0, NTHREADS - 32>(live);
        TSC(1);
        load_af(0, SM_SC + (cta >> 5) * 1024);
        load_af(1, SM_SC + (cta >> 5) * 1024 + 512);
        tfetch(T_A); tmma(acc, 0, T_A, true);
        tfetch(T_A + 1); tmma(acc, 1, T_A + 1, false);
        bar_sync<BAR_ZERO, 288>(live);
        publish(acc, pub + R_A);
        TSC(2);
        {
            const float xv[2][4] = {{lo16(xr0.x), hi16(xr0.x), lo16(xr0.y), hi16(xr0.y)},
                                    {lo16(xr1.x), hi16(xr1.x), lo16(xr1.y), hi16(xr1.y)}};
            float mb[2], den[2];
            ln_stats(xv, sbase + SM_ST, st_s, warp, lane0, live, mb, den, []() {});
            const float m = (tid >> 7) ? mb[1] : mb[0], dn = (tid >> 7) ? den[1] : den[0];
            ln0 = bfr(__fdividef(bfr(lo16(xw) - m), dn));
            ln1 = bfr(__fdividef(bfr(hi16(xw) - m), dn));
        }
    }
    if (secs & 2) {
        {
            const int b = tid >> 7, pr = tid & 127;
            const uint32_t* p = scr + ((cta >> 5) * 4 + (pr >> 5)) * RSZ + R_A + b * 64 + (pr & 31) * 2;
            uint32_t sa = sbase + SM_H + frag_off(b, pr * 2);
            PIN(p); PIN32(sa);
            TSC(3);
            uint2 v[8];
            gather<16 * RSZ>(v, tag, p);
            float sa0 = bfr((decf(v[0].x) + decf(v[2].x)) + (decf(v[4].x) + decf(v[6].x)));
            float sa1 = bfr((decf(v[0].y) + decf(v[2].y)) + (decf(v[4].y) + decf(v[6].y)));
            float ca0 = bfr((decf(v[1].x) + decf(v[3].x)) + (decf(v[5].x) + decf(v[7].x)));
            float ca1 = bfr((decf(v[1].y) + decf(v[3].y)) + (decf(v[5].y) + decf(v[7].y)));
            float h0 = bfr(ln0 * bfr(1.f + ca0)) + sa0, h1 = bfr(ln1 * bfr(1.f + ca1)) + sa1;
            sts32_p(sa, pack2(h0, h1), live);
            tscan(T_Q, 7);
            cbar();
        }
        TSC(4);
        load_af(0, SM_H);
        load_af(1, SM_H + 512);
        tfetch(T_Q);
        tfetch(T_Q + 1); tmma(acc, 0, T_Q, true);
        tfetch(T_Q + 2); tmma(acc2, 0, T_Q + 1, true);
        tmma(acc, 1, T_Q + 2, false);
        tfetch(T_Q + 3);
        publish(acc, pub + R_Q);
        tmma(acc2, 1, T_Q + 3, false);
        publish(acc2, pub + R_Q + 128);
        TSC(5);
#pragma unroll
        for (int j = 0; j < 3; j++) load_af(j, SM_SC + ((cta + 128 * j) / 48) * 512);
        tfetch(T_M); tmma(acc, 0, T_M, true);
        publish(acc, pub + R_M0);
        tfetch(T_M + 1); tmma(acc2, 1, T_M + 1, true);
        publish(acc2, pub + R_M1);
        tfetch(T_M + 2); tmma(acc, 2, T_M + 2, true);
        publish(acc, pub + R_M2);
        bar_arrive<BAR_MGO, 288>(live);
        TSC(6);
    }
    if (secs & 4) {
        {
            const uint32_t* p = scr + (((cta >> 4) & 3) * 8 + warp) * RSZ + R_Q + (lane >> 4) * 128 + (cta >> 6) * 64 + (lane & 15) * 4;
            uint4 v[4];
            gather<32 * RSZ>(v, tag, p);
            float q0 = (decf(v[0].x) + decf(v[1].x)) + (decf(v[2].x) + decf(v[3].x));
            float q1 = (decf(v[0].y) + decf(v[1].y)) + (decf(v[2].y) + decf(v[3].y));
            float q2f = (decf(v[0].z) + decf(v[1].z)) + (decf(v[2].z) + decf(v[3].z));
            float q3 = (decf(v[0].w) + decf(v[1].w)) + (decf(v[2].w) + decf(v[3].w));
            sts64_p(sbase + SM_Q + warp * 272 + lane * 8, pack2(q0, q1), pack2(q2f, q3), live);
            tscan(T_K, 4);
            cbar();
        }
        TSC(7);
        float s[4][2];
        load_af8(0, sbase + SM_Q + l7 * 272 + ljp * 16);
#pragma unroll
        for (int j = 0; j < 4; j++) {
            const float scale = 0.08838834764831845f;
            tfetch(T_K + j);
            tmma(acc, 0, T_K + j, true);
            s[j][0] = bfr(bfr(acc.s0()) * scale);
            s[j][1] = bfr(bfr(acc.s1()) * scale);
        }
        const uint32_t q0lane = live && (lane & 3) == 0;
        float m = fmaxf(fmaxf(fmaxf(s[0][0], s[0][1]), fmaxf(s[1][0], s[1][1])), fmaxf(fmaxf(s[2][0], s[2][1]), fmaxf(s[3][0], s[3][1])));
        m = fmaxf(m, __shfl_xor_sync(0xffffffffu, m, 1));
        m = fmaxf(m, __shfl_xor_sync(0xffffffffu, m, 2));
        sts32_p(sbase + SM_ST + (64 + g8 * 8 + warp) * 4, __float_as_uint(m), q0lane);
        cbar();
        {
            const float4 a = *reinterpret_cast<const float4*>(st_s + 64 + g8 * 8);
            const float4 b = *reinterpret_cast<const float4*>(st_s + 64 + g8 * 8 + 4);
            m = fmaxf(fmaxf(fmaxf(a.x, a.y), fmaxf(a.z, a.w)), fmaxf(fmaxf(b.x, b.y), fmaxf(b.z, b.w)));
        }
        float l = 0.f;
#pragma unroll
        for (int j = 0; j < 4; j++) {
            const float p0 = __expf(s[j][0] - m), p1 = __expf(s[j][1] - m);
            l += p0 + p1;
            sts32_p(sbase + SM_P + g8 * 528 + (j * 64 + warp * 8 + q2) * 2, pack2(p0, p1), live);
        }
        l += __shfl_xor_sync(0xffffffffu, l, 1);
        l += __shfl_xor_sync(0xffffffffu, l, 2);
        sts32_p(sbase + SM_ST + (128 + g8 * 8 + warp) * 4, __float_as_uint(l), q0lane);
        tscan(T_V, 4);
        cbar();
        {
            const float4 a = *reinterpret_cast<const float4*>(st_s + 128 + g8 * 8);
            const float4 b = *reinterpret_cast<const float4*>(st_s + 128 + g8 * 8 + 4);
            st2(mine + R_ML + g8 * 2, encf(m, tag), encf(((a.x + a.y) + (a.z + a.w)) + ((b.x + b.y) + (b.z + b.w)), tag),
                warp == 0 && q0lane);
        }
        bar_arrive<BAR_MGO, 288>(live);
        TSC(8);
    }
    if (secs & 8) {
        load_af8(0, sbase + SM_P + l7 * 528 + ljp * 16);
        load_af8(4, sbase + SM_P + l7 * 528 + ljp * 16 + 256);
        uint32_t* po = mine + R_O + g8 * 128 + warp * 8 + q2;
        uint32_t* pc = scr + (C_O + ((cta >> 4) & 3)) * RSZ + R_CNT;
        PIN(po); PIN(pc);
        tfetch(T_V); tmma(acc, 0, T_V, true);
        tfetch(T_V + 1); tmma(acc2, 0, T_V + 1, true);
        tfetch(T_V + 2); tmma(acc, 4, T_V + 2, false);
        st2(po, encf(acc.s0(), tag), encf(acc.s1(), tag), live);
        tfetch(T_V + 3); tmma(acc2, 4, T_V + 3, false);
        st2(po + 64, encf(acc2.s0(), tag), encf(acc2.s1(), tag), live);
        cnt_add(pc, lane0);
        TSC(10);
        const int h = cta >> 2, b = tid >> 7, d = tid & 127;
        const uint32_t* p = scr + (b * 64 + (h >> 3) * 16) * RSZ + R_O + (h & 7) * 128 + d;
        uint32_t so = sbase + SM_H + frag_off(b, d & ~1) + (d & 1) * 2;
        PIN(p); PIN32(so); PIN(px);
        if (warp == 3) cnt_wait(scr + (C_O + (h >> 3)) * RSZ + R_CNT, 64 * GATE_NUM);
        bar_sync<BAR_ALPHA, 288>(live);
        uint32_t v[16];
        gather<RSZ>(v, tag, p);
        float r[4];
#pragma unroll
        for (int j = 0; j < 4; j++) {
            const float4 a = *reinterpret_cast<const float4*>(st_s + 192 + b * 16 + j * 4);
            r[j] = (a.x * decf(v[4 * j]) + a.y * decf(v[4 * j + 1])) + (a.z * decf(v[4 * j + 2]) + a.w * decf(v[4 * j + 3]));
        }
        sts16_p(so, pack2((r[0] + r[1]) + (r[2] + r[3]), 0.f), live);
        tscan(T_WO, 4);
        cbar();
        TSC(11);
    }
    if (secs & 16) {
        load_af(0, SM_H);
        tfetch(T_WO);
        tfetch(T_WO + 1); tmma(acc, 0, T_WO, true);
        tfetch(T_WO + 2); tmma(acc2, 0, T_WO + 1, true);
        publish(acc, px);
        tmma(acc, 0, T_WO + 2, true);
        publish(acc2, px + 8 * RSZ);
        tfetch(T_WO + 3);
        publish(acc, px + 16 * RSZ);
        tmma(acc2, 0, T_WO + 3, true);
        publish(acc2, px + 24 * RSZ);
        cnt_add(scr + (C_X + (cta & 3)) * RSZ + R_CNT, lane0);
        TSC(12);
    }
    if (secs & 32) {
        ulonglong2 w[4];
        gatherf<4>(w, tag, [&](int i) { return scr + G_SC + tid * 8 + (i >> 1) * 2048 + (i & 1) * 4; });
        const uint32_t* p = scr + G_X2 + tid * 4;
        uint32_t so = sbase + SM_H2 + frag_off(0, tid * 4);
        PIN(p); PIN32(so);
        if (warp == 5) cnt_wait(scr + C_X2 * RSZ + R_CNT, 128);
        cbar();
        uint4 v[2];
        gather<1024>(v, tag, p);
        const float xv[2][4] = {{hi16(v[0].x), hi16(v[0].y), hi16(v[0].z), hi16(v[0].w)},
                                {hi16(v[1].x), hi16(v[1].y), hi16(v[1].z), hi16(v[1].w)}};
        float mb[2], den[2];
        ln_stats(xv, sbase + SM_ST, st_s, warp, lane0, live, mb, den, []() {});
#pragma unroll
        for (int b = 0; b < 2; b++) {
            float h[4];
#pragma unroll
            for (int i = 0; i < 4; i++) {
                const uint32_t sc = (uint32_t)(((i & 1) ? w[b * 2 + (i >> 1)].y : w[b * 2 + (i >> 1)].x) >> 32);
                h[i] = bfr(bfr(__fdividef(bfr(xv[b][i] - mb[b]), den[b])) * hi16(sc)) + lo16(sc);
            }
            sts32_p(so + b * 64, pack2(h[0], h[1]), live);
            sts32_p(so + b * 64 + 16, pack2(h[2], h[3]), live);
        }
        tscan(T_E, 7);
        cbar();
        TSC(13);
    }
    if (secs & 64) {
        const int r0 = (cta * 7) & 7, n0 = 8 - r0;
        float ga0 = 0.f, ga1 = 0.f, gb0 = 0.f, gb1 = 0.f;
        uint32_t* pch = scr + (C_H + ((cta & 63) >> 3)) * RSZ + R_CNT;
        PIN(pch);
#pragma unroll
        for (int j = 0; j < 7; j++) load_af(j, SM_H2 + ((r0 + j) & 7) * 512);
        tfetch(T_E);
#pragma unroll
        for (int j = 0; j < 7; j++) {
            Acc& a = (j & 1) ? acc2 : acc;
            if (j < 5) tfetch(T_E + 1 + j);
            tmma(a, j, T_E + j, true);
            if (j == 5) tfetch(T_E + 6);
            float t0, t1;
            a.pick(lj, t0, t1);
            const bool f = j < n0;
            ga0 += f ? t0 : 0.f; ga1 += f ? t1 : 0.f;
            gb0 += f ? 0.f : t0; gb1 += f ? 0.f : t1;
        }
        publish2(ga0, ga1, pub + R_H);
        publish2(gb0, gb1, pub + R_H + 128);
        cnt_add(pch, lane0);
        TSC(14);
    }
    if (secs & 128) {
        {
            const int wq = warp < 7 ? warp : 6;
            const int b = (lane >> 4) & 1, q4 = (lane & 15) * 4;
            const int pg = (cta >> 4) * 8 + wq;
            const uint32_t* p0 = scr + pg * RSZ + R_H + (wq == 0 ? 0 : 128) + b * 64 + q4;
            const uint32_t* p1 = scr + (pg + 1) * RSZ + R_H + b * 64 + q4;
            const int k = wq * 64 + q4, kb = k / 112, kk = k - kb * 112;
            uint32_t so = sbase + SM_HH + kb * 512 + frag_off(b, kk);
            PIN(p0); PIN(p1); PIN32(so); PIN(py);
            if (warp == 7) cnt_wait(scr + (C_H + (cta >> 4)) * RSZ + R_CNT, 32 * GATE_NUM);
            cbar();
            uint4 v[4];
            gatherf<4>(v, tag, [&](int i) { return ((i & 1) ? p1 : p0) + (i >> 1) * 64 * RSZ; });
            float g[4] = {decf(v[0].x) + decf(v[1].x), decf(v[0].y) + decf(v[1].y), decf(v[0].z) + decf(v[1].z),
                          decf(v[0].w) + decf(v[1].w)};
            float u[4] = {decf(v[2].x) + decf(v[3].x), decf(v[2].y) + decf(v[3].y), decf(v[2].z) + decf(v[3].z),
                          decf(v[2].w) + decf(v[3].w)};
            float r[4];
#pragma unroll
            for (int i = 0; i < 4; i++) r[i] = bfr(silu_f(bfr(g[i]))) * bfr(u[i]);
            sts32_p(so, pack2(r[0], r[1]), live);
            sts32_p(so + 16, pack2(r[2], r[3]), live);
            tscan(T_GB, 5);
            load_af(4, SM_SC + (cta >> 4) * 512);
            tfetch(T_GB);
            cbar();
        }
        TSC(15);
#pragma unroll
        for (int j = 0; j < 4; j++) load_af(j, SM_HH + j * 512);
        tfetch(T_F); tmma(acc2, 4, T_GB, true);
        tfetch(T_F + 1); tmma(acc, 0, T_F, true);
        publish(acc2, py + (R_GB - R_Y));
        bar_arrive<BAR_XGO, 288>(live);
        tfetch(T_F + 2); tmma(acc, 1, T_F + 1, false);
        tmma(acc, 2, T_F + 2, false);
        tfetch(T_F + 3); tmma(acc, 3, T_F + 3, false);
        publish(acc, py);
        TSC(16);
    }
    }
}

#define L2PROMO CU_TENSOR_MAP_L2_PROMOTION_L2_256B
typedef CUresult (*EncodeFn)(CUtensorMap*, CUtensorMapDataType, cuuint32_t, void*, const cuuint64_t*,
                             const cuuint64_t*, const cuuint32_t*, const cuuint32_t*, CUtensorMapInterleave,
                             CUtensorMapSwizzle, CUtensorMapL2promotion, CUtensorMapFloatOOBfill);

void make_map(EncodeFn fn, CUtensorMap* m, const void* base, uint64_t rows, uint64_t cols, uint32_t box_rows) {
    cuuint64_t gd[3] = {cols, rows, 1};
    cuuint64_t gs[2] = {cols * 2, cols * 2 * rows};
    cuuint32_t bx[3] = {64, box_rows, 1};
    cuuint32_t es[3] = {1, 1, 1};
    fn(m, CU_TENSOR_MAP_DATA_TYPE_BFLOAT16, 3, const_cast<void*>(base), gd, gs, bx, es,
       CU_TENSOR_MAP_INTERLEAVE_NONE, CU_TENSOR_MAP_SWIZZLE_128B, L2PROMO, CU_TENSOR_MAP_FLOAT_OOB_FILL_NONE);
}
void make_map_k(EncodeFn fn, CUtensorMap* m, const void* base, uint64_t rows) {
    cuuint64_t gd[3] = {64, rows, 2};
    cuuint64_t gs[2] = {256, 128};
    cuuint32_t bx[3] = {64, 64, 2};
    cuuint32_t es[3] = {1, 1, 1};
    fn(m, CU_TENSOR_MAP_DATA_TYPE_BFLOAT16, 3, const_cast<void*>(base), gd, gs, bx, es,
       CU_TENSOR_MAP_INTERLEAVE_NONE, CU_TENSOR_MAP_SWIZZLE_128B, L2PROMO, CU_TENSOR_MAP_FLOAT_OOB_FILL_NONE);
}

}

extern "C" void kernel_launch(void* const* d_in, const int* in_sizes, int n_in, void* d_out, int out_size) {
    (void)in_sizes; (void)n_in; (void)out_size;
    static EncodeFn enc_fn = nullptr;
    if (!enc_fn) {
        cudaDriverEntryPointQueryResult qr;
        void* fn = nullptr;
        cudaGetDriverEntryPoint("cuTensorMapEncodeTiled", &fn, cudaEnableDefault, &qr);
        enc_fn = (EncodeFn)fn;
        cudaFuncSetAttribute(fused_kernel, cudaFuncAttributeMaxDynamicSharedMemorySize, SM_TOTAL);
    }
    Maps maps;
    make_map(enc_fn, &maps.mod, d_in[10], 1024, 6144, 128);
    make_map(enc_fn, &maps.wq, d_in[3], 1024, 4096, 128);
    make_map_k(enc_fn, &maps.k, d_in[1], (uint64_t)8 * SK);
    make_map(enc_fn, &maps.v, d_in[2], (uint64_t)8 * SK, 128, 128);
    make_map(enc_fn, &maps.wo, d_in[4], 4096, 1024, 128);
    make_map(enc_fn, &maps.w1, d_in[6], 1024, 3584, 128);
    make_map(enc_fn, &maps.w3, d_in[7], 1024, 3584, 128);
    make_map(enc_fn, &maps.w2, d_in[8], 3584, 1024, 112);
    fused_kernel<<<NCTA, NTHREADS, SM_TOTAL>>>(maps, (const __nv_bfloat16*)d_in[0], (const __nv_bfloat16*)d_in[9],
                                               (__nv_bfloat16*)d_out, (const __nv_bfloat16*)d_in[10],
                                               (const __nv_bfloat16*)d_in[3]);
}
```

```cpp
#include <cuda_runtime.h>
#include <cuda_bf16.h>
#include <cuda.h>
#include <stdint.h>

namespace {

constexpr int NCTA = 128;
constexpr int NSTAGE = 12;
constexpr int STAGE_BYTES = 16384;
constexpr int NBOX = 33;
constexpr int PACE_3 = 660, PACE_4 = 760, PACE_5 = 950;
constexpr int NFIRST = 2;
constexpr int NTHREADS = 320;
constexpr int SK = 32768, WIN = 4096;

constexpr int R_A = 0;
constexpr int R_M = 128;
constexpr int R_Y = 256;
constexpr int R_ML = 384;
constexpr int R_CNT = 416;
constexpr int R_CLR = 448;
constexpr int R_Q = 448;
constexpr int R_O = 704;
constexpr int R_X = 1728;
constexpr int R_H = 2240;
constexpr int RSZ = 2496;
constexpr int X2_COPIES = 4;
constexpr int C_O = 0, C_X = 4, C_X2 = 8, C_H = 16;
constexpr int T_A = 0, T_Q = 2, T_M = 6, T_K = 10, T_V = 14, T_WO = 18, T_E = 22, T_F = 29;
constexpr int G_X2 = NCTA * RSZ;
constexpr int G_SC = G_X2 + 2048 * X2_COPIES;

__device__ __align__(1024) uint32_t g_scr[G_SC + 4096];
__device__ unsigned int g_epoch;

#define UNLIKELY(x) __builtin_expect(!!(x), 0)
#define PIN(p) asm volatile("" : "+l"(p))
#define PIN32(p) asm volatile("" : "+r"(p))

struct Maps {
    CUtensorMap mod, wq, k, v, wo, w1, w3, w2;
};

constexpr int SM_RING = 0;
constexpr int SM_SC = NSTAGE * STAGE_BYTES;
constexpr int SM_H2 = SM_SC + 4096;
constexpr int SM_H = SM_H2 + 4096;
constexpr int SM_HH = SM_H + 1024;
constexpr int SM_Q = SM_HH + 2048;
constexpr int SM_P = SM_Q + 8 * 272;
constexpr int SM_ST = SM_P + 8 * 528;
constexpr int SM_TAB = SM_ST + 1024;
constexpr int SM_BAR = SM_TAB + 1024;
constexpr int SM_TOTAL = SM_BAR + 2 * NSTAGE * 8;

constexpr unsigned SPIN_LIMIT = 1u << 20;

#define PRED(n) "{\n.reg .pred p;\nsetp.ne.u32 p, %" #n ", 0;\n@p "

__device__ __forceinline__ uint32_t smem_u32(const void* p) { return (uint32_t)__cvta_generic_to_shared(p); }
__device__ __forceinline__ void mbar_init(uint32_t a, uint32_t c) {
    asm volatile("mbarrier.init.shared::cta.b64 [%0], %1;" ::"r"(a), "r"(c) : "memory");
}
__device__ __forceinline__ void mbar_expect(uint32_t a, uint32_t bytes) {
    asm volatile("mbarrier.arrive.expect_tx.shared::cta.b64 _, [%0], %1;" ::"r"(a), "r"(bytes) : "memory");
}
__device__ __forceinline__ void mbar_arrive_p(uint32_t a, uint32_t pred) {
    asm volatile(PRED(1) "mbarrier.arrive.shared::cta.b64 _, [%0];\n}" ::"r"(a), "r"(pred) : "memory");
}
__device__ __forceinline__ uint32_t mbar_try(uint32_t a, uint32_t parity) {
    uint32_t done;
    asm volatile(
        "{\n.reg .pred p;\nmbarrier.try_wait.parity.shared::cta.b64 p, [%1], %2;\nselp.u32 %0, 1, 0, p;\n}"
        : "=r"(done) : "r"(a), "r"(parity) : "memory");
    return done;
}
__device__ __forceinline__ uint32_t mbar_test_p(uint32_t a, uint32_t parity, uint32_t pred) {
    uint32_t done;
    asm volatile(
        "{\n.reg .pred p, q;\nsetp.ne.u32 p, %3, 0;\nsetp.ne.u32 q, %3, %3;\n"
        "@p mbarrier.test_wait.parity.shared::cta.b64 q, [%1], %2;\nselp.u32 %0, 1, 0, q;\n}"
        : "=r"(done) : "r"(a), "r"(parity), "r"(pred) : "memory");
    return done;
}
__device__ __forceinline__ void mbar_wait(uint32_t a, uint32_t parity) {
    unsigned n = 0;
    while (!mbar_try(a, parity) && ++n < SPIN_LIMIT) {}
}
__device__ __noinline__ void mbar_wait_slow(uint32_t a, uint32_t parity) { mbar_wait(a, parity); }
__device__ __forceinline__ void tma3d(uint32_t dst, const void* m, int c0, int c1, uint32_t bar, uint64_t pol) {
    asm volatile(
        "cp.async.bulk.tensor.3d.shared::cluster.global.mbarrier::complete_tx::bytes.L2::cache_hint"
        " [%0], [%1, {%3, %4, %5}], [%2], %6;"
        ::"r"(dst), "l"(m), "r"(bar), "r"(c0), "r"(c1), "r"(0), "l"(pol) : "memory");
}
__device__ __forceinline__ void ldsm4(uint32_t (&r)[4], uint32_t a) {
    asm volatile("ldmatrix.sync.aligned.m8n8.x4.shared.b16 {%0,%1,%2,%3}, [%4];"
                 : "=r"(r[0]), "=r"(r[1]), "=r"(r[2]), "=r"(r[3]) : "r"(a) : "memory");
}
__device__ __forceinline__ void ldsm4t(uint32_t (&r)[4], uint32_t a) {
    asm volatile("ldmatrix.sync.aligned.m8n8.x4.trans.shared.b16 {%0,%1,%2,%3}, [%4];"
                 : "=r"(r[0]), "=r"(r[1]), "=r"(r[2]), "=r"(r[3]) : "r"(a) : "memory");
}
__device__ __forceinline__ void lds128(uint32_t (&r)[4], uint32_t a) {
    asm volatile("ld.shared.v4.u32 {%0,%1,%2,%3}, [%4];"
                 : "=r"(r[0]), "=r"(r[1]), "=r"(r[2]), "=r"(r[3]) : "r"(a) : "memory");
}
__device__ __forceinline__ void mma16816(float (&c)[4], const uint32_t (&a)[4], uint32_t b0, uint32_t b1) {
    asm volatile(
        "mma.sync.aligned.m16n8k16.row.col.f32.bf16.bf16.f32 {%0,%1,%2,%3}, {%4,%5,%6,%7}, {%8,%9}, {%0,%1,%2,%3};"
        : "+f"(c[0]), "+f"(c[1]), "+f"(c[2]), "+f"(c[3])
        : "r"(a[0]), "r"(a[1]), "r"(a[2]), "r"(a[3]), "r"(b0), "r"(b1));
}
__device__ __forceinline__ void mma16816_z(float (&c)[4], const uint32_t (&a)[4], uint32_t b0, uint32_t b1) {
    asm volatile(
        "mma.sync.aligned.m16n8k16.row.col.f32.bf16.bf16.f32 {%0,%1,%2,%3}, {%4,%5,%6,%7}, {%8,%9}, {%10,%10,%10,%10};"
        : "=f"(c[0]), "=f"(c[1]), "=f"(c[2]), "=f"(c[3])
        : "r"(a[0]), "r"(a[1]), "r"(a[2]), "r"(a[3]), "r"(b0), "r"(b1), "f"(0.f));
}
template <int ID, int N> __device__ __forceinline__ void bar_sync() {
    asm volatile("bar.sync %0, %1;" ::"n"(ID), "n"(N) : "memory");
}
template <int ID, int N> __device__ __forceinline__ void bar_arrive() {
    asm volatile("bar.arrive %0, %1;" ::"n"(ID), "n"(N) : "memory");
}
__device__ __forceinline__ void cbar() { bar_sync<1, 256>(); }
constexpr int BAR_ALPHA = 2, BAR_XGO = 3, BAR_MGO = 4, BAR_ZERO = 5;

__device__ __forceinline__ uint32_t pack2(float lo, float hi) {
    uint32_t r;
    asm("cvt.rn.bf16x2.f32 %0, %1, %2;" : "=r"(r) : "f"(hi), "f"(lo));
    return r;
}
__device__ __forceinline__ float bfr(float x) { return __uint_as_float(pack2(0.f, x)); }
__device__ __forceinline__ float lo16(uint32_t w) { return __uint_as_float(w << 16); }
__device__ __forceinline__ float hi16(uint32_t w) { return __uint_as_float(w & 0xffff0000u); }

__device__ __forceinline__ uint32_t encf(float v, uint32_t tag) { return (__float_as_uint(v) & ~3u) | tag; }
__device__ __forceinline__ float decf(uint32_t w) { return __uint_as_float(w & ~3u); }
__device__ __forceinline__ void st2(uint32_t* p, uint32_t a, uint32_t b, uint32_t pred) {
    asm volatile(PRED(3) "st.relaxed.gpu.global.v2.u32 [%0], {%1,%2};\n}" ::"l"(p), "r"(a), "r"(b), "r"(pred) : "memory");
}
__device__ __forceinline__ void st4(uint32_t* p, uint32_t a, uint32_t b, uint32_t c, uint32_t d, uint32_t pred) {
    asm volatile(PRED(5) "st.relaxed.gpu.global.v4.u32 [%0], {%1,%2,%3,%4};\n}"
                 ::"l"(p), "r"(a), "r"(b), "r"(c), "r"(d), "r"(pred) : "memory");
}
__device__ __forceinline__ void st64x2(uint32_t* p, uint64_t a, uint64_t b, uint32_t pred) {
    asm volatile(PRED(3) "st.relaxed.gpu.global.v2.u64 [%0], {%1,%2};\n}" ::"l"(p), "l"(a), "l"(b), "r"(pred) : "memory");
}
__device__ __forceinline__ void sts16_p(uint32_t a, uint32_t v, uint32_t pred) {
    asm volatile(PRED(2) "st.shared.u16 [%0], %1;\n}" ::"r"(a), "h"((uint16_t)v), "r"(pred) : "memory");
}
__device__ __forceinline__ void sts32_p(uint32_t a, uint32_t v, uint32_t pred) {
    asm volatile(PRED(2) "st.shared.u32 [%0], %1;\n}" ::"r"(a), "r"(v), "r"(pred) : "memory");
}
__device__ __forceinline__ void sts64_p(uint32_t a, uint32_t x, uint32_t y, uint32_t pred) {
    asm volatile(PRED(3) "st.shared.v2.u32 [%0], {%1,%2};\n}" ::"r"(a), "r"(x), "r"(y), "r"(pred) : "memory");
}
__device__ __forceinline__ void sts128_p(uint32_t a, float x, float y, float z, float w, uint32_t pred) {
    asm volatile(PRED(5) "st.shared.v4.f32 [%0], {%1,%2,%3,%4};\n}"
                 ::"r"(a), "f"(x), "f"(y), "f"(z), "f"(w), "r"(pred) : "memory");
}
__device__ __forceinline__ void ldx(uint4& v, const uint32_t* p) {
    asm volatile("ld.relaxed.gpu.global.v4.u32 {%0,%1,%2,%3}, [%4];"
                 : "=r"(v.x), "=r"(v.y), "=r"(v.z), "=r"(v.w) : "l"(p) : "memory");
}
__device__ __forceinline__ void ldx(uint2& v, const uint32_t* p) {
    asm volatile("ld.relaxed.gpu.global.v2.u32 {%0,%1}, [%2];" : "=r"(v.x), "=r"(v.y) : "l"(p) : "memory");
}
__device__ __forceinline__ void ldx(uint32_t& v, const uint32_t* p) {
    asm volatile("ld.relaxed.gpu.global.u32 %0, [%1];" : "=r"(v) : "l"(p) : "memory");
}
__device__ __forceinline__ void ldx(ulonglong2& v, const uint32_t* p) {
    asm volatile("ld.relaxed.gpu.global.v2.u64 {%0,%1}, [%2];" : "=l"(v.x), "=l"(v.y) : "l"(p) : "memory");
}
__device__ __forceinline__ uint32_t andw(const uint4& v) { return v.x & v.y & v.z & v.w; }
__device__ __forceinline__ uint32_t andw(const uint2& v) { return v.x & v.y; }
__device__ __forceinline__ uint32_t andw(const uint32_t& v) { return v; }
__device__ __forceinline__ uint32_t andw(const ulonglong2& v) { return (uint32_t)v.x & (uint32_t)v.y; }

template <int N, typename T, typename F, typename G>
__device__ __forceinline__ void gatherf(T (&v)[N], uint32_t tag, F addr, G meanwhile) {
    uint32_t all = tag;
#pragma unroll
    for (int i = 0; i < N; i++) ldx(v[i], addr(i));
    meanwhile();
#pragma unroll
    for (int i = 0; i < N; i++) all &= andw(v[i]);
    if (UNLIKELY(!__all_sync(0xffffffffu, all))) {
#pragma unroll 1
        for (unsigned n = 0; n < SPIN_LIMIT; n++) {
            uint32_t bad = 0;
#pragma unroll
            for (int i = 0; i < N; i++) bad |= (andw(v[i]) & tag) ? 0u : 1u << i;
            bad = __reduce_or_sync(0xffffffffu, bad);
            if (!bad) break;
#pragma unroll
            for (int i = 0; i < N; i++)
                if (bad & (1u << i)) ldx(v[i], addr(i));
        }
    }
}
template <int STRIDE, int N, typename T>
__device__ __forceinline__ void poll(T (&v)[N], uint32_t tag, const uint32_t* p) {
    unsigned n = 0;
    bool ok;
    do {
        uint32_t all = tag;
#pragma unroll
        for (int i = 0; i < N; i++) ldx(v[i], p + i * STRIDE);
#pragma unroll
        for (int i = 0; i < N; i++) all &= andw(v[i]);
        ok = __all_sync(0xffffffffu, all);
    } while (!ok && ++n < SPIN_LIMIT);
}
template <int STRIDE, int N, typename T, typename G>
__device__ __forceinline__ void gather(T (&v)[N], uint32_t tag, const uint32_t* p, G meanwhile) {
    gatherf<N>(v, tag, [&](int i) { return p + i * STRIDE; }, meanwhile);
}
template <int STRIDE, int N, typename T>
__device__ __forceinline__ void gather(T (&v)[N], uint32_t tag, const uint32_t* p) {
    gather<STRIDE>(v, tag, p, []() {});
}
__device__ __forceinline__ void cnt_wait(const uint32_t* p, uint32_t target) {
    uint32_t v;
    unsigned n = 0;
    do { ldx(v, p); } while (v < target && ++n < SPIN_LIMIT);
}
__device__ __forceinline__ void cnt_add(uint32_t* p_plus_lane, uint32_t lane0) {
    asm volatile(PRED(1) "red.relaxed.gpu.global.add.u32 [%0], %1;\n}" ::"l"(p_plus_lane), "r"(lane0) : "memory");
}

__device__ __forceinline__ int frag_off(int b, int k) {
    return (k >> 5) * 128 + b * 64 + ((k >> 1) & 3) * 16 + ((k >> 3) & 1) * 8 + ((k >> 4) & 1) * 4;
}

struct Acc {
    float c[8][4];
    __device__ __forceinline__ float s0() const { return (c[0][0] + c[1][2]) + (c[2][0] + c[3][2]); }
    __device__ __forceinline__ float s1() const { return (c[0][1] + c[1][3]) + (c[2][1] + c[3][3]); }
    __device__ __forceinline__ void pick(int r, float& v0, float& v1) const {
        const bool o = r & 1, h = r & 2;
        const float e0 = h ? (o ? c[6][0] : c[4][0]) : (o ? c[2][0] : c[0][0]);
        const float e1 = h ? (o ? c[6][1] : c[4][1]) : (o ? c[2][1] : c[0][1]);
        const float d0 = h ? (o ? c[7][2] : c[5][2]) : (o ? c[3][2] : c[1][2]);
        const float d1 = h ? (o ? c[7][3] : c[5][3]) : (o ? c[3][3] : c[1][3]);
        v0 = e0 + d0;
        v1 = e1 + d1;
    }
};

__device__ __forceinline__ void ln_stats(const float (&x)[2][4], uint32_t st_addr, const float* st, int warp,
                                         uint32_t lane0, float (&mb)[2], float (&den)[2]) {
    float r[4], piv[2];
#pragma unroll
    for (int b = 0; b < 2; b++) {
        piv[b] = __shfl_sync(0xffffffffu, x[b][0], 0);
        float d0 = x[b][0] - piv[b], d1 = x[b][1] - piv[b], d2 = x[b][2] - piv[b], d3 = x[b][3] - piv[b];
        r[b * 2] = (d0 + d1) + (d2 + d3);
        r[b * 2 + 1] = (d0 * d0 + d1 * d1) + (d2 * d2 + d3 * d3);
    }
#pragma unroll
    for (int o = 1; o < 32; o <<= 1)
#pragma unroll
        for (int i = 0; i < 4; i++) r[i] += __shfl_xor_sync(0xffffffffu, r[i], o);
    sts128_p(st_addr + warp * 16, piv[0] + r[0] * (1.f / 128.f), r[1] - r[0] * r[0] * (1.f / 128.f),
             piv[1] + r[2] * (1.f / 128.f), r[3] - r[2] * r[2] * (1.f / 128.f), lane0);
    cbar();
    float4 t[8];
#pragma unroll
    for (int w = 0; w < 8; w++) t[w] = *reinterpret_cast<const float4*>(st + w * 4);
    const float m0 = (((t[0].x + t[1].x) + (t[2].x + t[3].x)) + ((t[4].x + t[5].x) + (t[6].x + t[7].x))) * 0.125f;
    const float m1 = (((t[0].z + t[1].z) + (t[2].z + t[3].z)) + ((t[4].z + t[5].z) + (t[6].z + t[7].z))) * 0.125f;
#pragma unroll
    for (int w = 0; w < 8; w++) {
        t[w].y += 128.f * (t[w].x - m0) * (t[w].x - m0);
        t[w].w += 128.f * (t[w].z - m1) * (t[w].z - m1);
    }
    const float v0 = (((t[0].y + t[1].y) + (t[2].y + t[3].y)) + ((t[4].y + t[5].y) + (t[6].y + t[7].y))) * (1.f / 1024.f);
    const float v1 = (((t[0].w + t[1].w) + (t[2].w + t[3].w)) + ((t[4].w + t[5].w) + (t[6].w + t[7].w))) * (1.f / 1024.f);
    mb[0] = bfr(m0);
    mb[1] = bfr(m1);
    float s0, s1;
    asm("sqrt.rn.ftz.f32 %0, %1;" : "=f"(s0) : "f"(bfr(bfr(fmaxf(v0, 0.f)) + 1e-5f)));
    asm("sqrt.rn.ftz.f32 %0, %1;" : "=f"(s1) : "f"(bfr(bfr(fmaxf(v1, 0.f)) + 1e-5f)));
    den[0] = bfr(s0);
    den[1] = bfr(s1);
}

__device__ __forceinline__ float silu_f(float x) { return __fdividef(x, 1.f + __expf(-x)); }
__device__ __forceinline__ float silu_x(float x) { return x / (1.f + expf(-x)); }

__global__ void __launch_bounds__(NTHREADS, 1)
fused_kernel(const __grid_constant__ Maps maps, const __nv_bfloat16* __restrict__ x_in,
             const __nv_bfloat16* __restrict__ c_in, __nv_bfloat16* __restrict__ out) {
    extern __shared__ __align__(1024) unsigned char smem[];
    const int tid = threadIdx.x, lane = tid & 31;
    const int warp = __shfl_sync(0xffffffffu, tid >> 5, 0);
    const int cta = blockIdx.x;
    const uint32_t sbase = smem_u32(smem);
    uint32_t* const scr = g_scr;
    uint32_t* const mine = g_scr + cta * RSZ;

    if (warp == 8) {
        uint32_t tlast;
        asm volatile("mov.u32 %0, %%globaltimer_lo;" : "=r"(tlast));
        uint64_t pol;
        asm volatile("createpolicy.fractional.L2::evict_first.b64 %0, 1.0;" : "=l"(pol));
        if (lane == 0) {
#pragma unroll
            for (int i = 0; i < NFIRST; i++) mbar_init(sbase + SM_BAR + i * 8, 1);
            asm volatile("fence.mbarrier_init.release.cluster;" ::: "memory");
#pragma unroll
            for (int i = 0; i < NFIRST; i++) {
                mbar_expect(sbase + SM_BAR + i * 8, 16384);
                tma3d(sbase + SM_RING + i * STAGE_BYTES, &maps.mod, (cta & 31) * 64, (cta >> 5) * 256 + i * 128,
                      sbase + SM_BAR + i * 8, pol);
            }
#pragma unroll
            for (int i = NFIRST; i < 2 * NSTAGE; i++) mbar_init(sbase + SM_BAR + i * 8, i < NSTAGE ? 1 : 8);
            asm volatile("fence.mbarrier_init.release.cluster;" ::: "memory");
        }
        __syncwarp();
        bar_arrive<0, 288>();
        {
            const int it = lane + 1;
            const int kvrow = (cta >> 4) * SK + (SK - WIN) + (cta & 15) * 256;
            int m, c0, c1;
            if (it < T_Q) {
                m = 0; c0 = (cta & 31) * 64; c1 = (cta >> 5) * 256 + it * 128;
            } else if (it < T_M) {
                int j = it - T_Q;
                m = 1; c0 = (cta & 31) * 128 + (j & 1) * 64; c1 = (cta >> 5) * 256 + (j >> 1) * 128;
            } else if (it < T_K) {
                m = 0; c0 = 2048 + (cta & 63) * 64; c1 = (cta >> 6) * 512 + (it - T_M) * 128;
            } else if (it < T_V) {
                m = 2; c0 = 0; c1 = kvrow + (it - T_K) * 64;
            } else if (it < T_WO) {
                int j = it - T_V;
                m = 3; c0 = (j & 1) * 64; c1 = kvrow + (j >> 1) * 128;
            } else if (it < T_E) {
                m = 4; c0 = (cta & 3) * 256 + (it - T_WO) * 64; c1 = (cta >> 2) * 128;
            } else if (it < T_F) {
                int g = cta * 7 + (it - T_E);
                int col = g >> 3;
                m = col < 56 ? 5 : 6;
                c0 = (col < 56 ? col : col - 56) * 64; c1 = (g & 7) * 128;
            } else {
                m = 7; c0 = (cta & 15) * 64; c1 = (cta >> 4) * 448 + (it - T_F) * 112;
            }
            *reinterpret_cast<int4*>(smem + SM_TAB + it * 16) = make_int4(m * 128, c0, c1, it >= T_F ? 14336 : 16384);
        }
        __syncwarp();
        if (lane == 0) {
            int stage = NFIRST;
            uint32_t phase = 1;
            tlast += ((cta * 37) & 127) * PACE_3 / 128 - PACE_3 / 2;
#pragma unroll 1
            for (int it = NFIRST; it < NBOX; it++) {
                const int4 e = *reinterpret_cast<const int4*>(smem + SM_TAB + it * 16);
                const uint32_t bar = sbase + SM_BAR + stage * 8;
                if (it >= NSTAGE) mbar_wait(bar + NSTAGE * 8, phase);
                {
                    auto landed = [&](int d) -> bool {
                        if (it < d) return true;
                        const int qs = stage >= d ? stage - d : stage - d + NSTAGE;
                        return mbar_test_p(sbase + SM_BAR + qs * 8, stage >= d ? phase ^ 1 : phase, 1);
                    };
                    uint32_t now;
                    for (unsigned n = 0; n < SPIN_LIMIT; n++) {
                        asm volatile("mov.u32 %0, %%globaltimer_lo;" : "=r"(now));
                        const int el = (int)(now - tlast);
                        if (landed(el >= PACE_5 ? 5 : el >= PACE_4 ? 4 : el >= PACE_3 ? 3 : 2)) break;
                    }
                    tlast = now;
                }
                if (it < 8) asm volatile("prefetch.tensormap [%0];" ::"l"(reinterpret_cast<const char*>(&maps) + it * 128) : "memory");
                mbar_expect(bar, e.w);
                tma3d(sbase + SM_RING + stage * STAGE_BYTES, reinterpret_cast<const char*>(&maps) + e.x, e.y, e.z, bar, pol);
                if (++stage == NSTAGE) { stage = 0; phase ^= 1; }
            }
        }
        return;
    }

    const unsigned epoch = *reinterpret_cast<volatile unsigned int*>(&g_epoch);

    if (warp == 9) {
        const int b = (lane >> 1) & 1, c4 = (lane & 1) * 4;
        const uint2 xr = *reinterpret_cast<const uint2*>(x_in + b * 1024 + cta * 8 + c4);
        for (int i = lane; i < R_CLR / 4; i += 32) st4(mine + i * 4, 0, 0, 0, 0, 1);
        uint32_t* px2 = scr + G_X2 + ((lane >> 2) % X2_COPIES) * 2048 + b * 1024 + cta * 8 + c4;
        uint32_t* const psc = scr + G_SC + (b * 1024 + cta * 8 + c4) * 2 + ((lane >> 2) & 1) * 4;
        asm volatile("fence.acq_rel.gpu;" ::: "memory");
        __syncwarp();
        bar_arrive<BAR_ZERO, 288>();
        const uint32_t tag = 1 + (epoch & 1);
        const int coff = b * 64 + (cta & 7) * 8 + c4;
        const float xv[4] = {lo16(xr.x), hi16(xr.x), lo16(xr.y), hi16(xr.y)};
        auto red8 = [&](float (&v)[4]) {
#pragma unroll
            for (int o = 4; o < 32; o <<= 1)
#pragma unroll
                for (int i = 0; i < 4; i++) v[i] += __shfl_xor_sync(0xffffffffu, v[i], o);
        };
        {
            auto gentle = [&](const uint32_t* p) -> uint4 {
                uint4 v;
                for (unsigned n = 0; n < SPIN_LIMIT; n++) {
                    __nanosleep(300);
                    ldx(v, p);
                    if (__all_sync(0xffffffffu, andw(v) & tag)) break;
                }
                return v;
            };
            float ga[4], gb[4], x2[4];
            bar_sync<BAR_MGO, 288>();
            {
                const uint4 v = gentle(scr + ((lane >> 2) * 16 + (cta >> 3)) * RSZ + R_M + coff);
                float md[4] = {decf(v.x), decf(v.y), decf(v.z), decf(v.w)};
                uint64_t pk[4];
#pragma unroll
                for (int i = 0; i < 4; i++) {
                    md[i] = bfr(md[i] + __shfl_xor_sync(0xffffffffu, md[i], 16));
                    ga[i] = __shfl_sync(0xffffffffu, md[i], lane & 3);
                    const float sbv = __shfl_sync(0xffffffffu, md[i], (lane & 3) + 4);
                    const float cbv = __shfl_sync(0xffffffffu, md[i], (lane & 3) + 8);
                    gb[i] = __shfl_sync(0xffffffffu, md[i], (lane & 3) + 12);
                    pk[i] = ((uint64_t)pack2(sbv, 1.f + cbv) << 32) | tag;
                }
                st64x2(psc, lane < 4 ? pk[0] : pk[2], lane < 4 ? pk[1] : pk[3], lane < 8);
            }
            {
                const int h = cta >> 2;
                const uint32_t* p = scr + ((lane >> 4) * 64 + (h >> 3) * 16 + (lane & 15)) * RSZ + R_ML + (h & 7) * 2;
                uint2 ml;
                bar_sync<BAR_MGO, 288>();
                for (unsigned n = 0; n < SPIN_LIMIT; n++) {
                    __nanosleep(300);
                    ldx(ml, p);
                    if (__all_sync(0xffffffffu, ml.x & ml.y & tag)) break;
                }
                float m = decf(ml.x), l = decf(ml.y);
                float M = m;
#pragma unroll
                for (int o = 1; o < 16; o <<= 1) M = fmaxf(M, __shfl_xor_sync(0xffffffffu, M, o));
                float w = __expf(m - M);
                float L = w * l;
#pragma unroll
                for (int o = 1; o < 16; o <<= 1) L += __shfl_xor_sync(0xffffffffu, L, o);
                sts32_p(sbase + SM_ST + (192 + lane) * 4, __float_as_uint(__fdividef(w, L)), 1);
                __syncwarp();
                bar_arrive<BAR_ALPHA, 288>();
            }
            {
                const uint32_t* p = mine + R_X + lane * 4;
                uint32_t* pc = scr + (C_X2 + (lane % X2_COPIES)) * RSZ + R_CNT;
                uint32_t lane0 = lane < X2_COPIES;
                PIN(p); PIN(px2); PIN(pc); PIN32(lane0);
                cnt_wait(scr + (C_X + (cta >> 5)) * RSZ + R_CNT, 32 * 8);
                uint4 v[4];
                poll<128>(v, tag, p);
                float s[4];
                s[0] = (decf(v[0].x) + decf(v[1].x)) + (decf(v[2].x) + decf(v[3].x));
                s[1] = (decf(v[0].y) + decf(v[1].y)) + (decf(v[2].y) + decf(v[3].y));
                s[2] = (decf(v[0].z) + decf(v[1].z)) + (decf(v[2].z) + decf(v[3].z));
                s[3] = (decf(v[0].w) + decf(v[1].w)) + (decf(v[2].w) + decf(v[3].w));
                red8(s);
#pragma unroll
                for (int i = 0; i < 4; i++) x2[i] = bfr(xv[i] + bfr(ga[i] * bfr(s[i])));
                st4(px2, __float_as_uint(x2[0]) | tag, __float_as_uint(x2[1]) | tag, __float_as_uint(x2[2]) | tag,
                    __float_as_uint(x2[3]) | tag, lane < 4 * X2_COPIES);
                cnt_add(pc, lane0);
            }
            if (cta == 0 && lane == 0) *reinterpret_cast<volatile unsigned int*>(&g_epoch) = epoch + 1;
            {
                const uint32_t* p = mine + R_Y + lane * 4;
                uint32_t* po = reinterpret_cast<uint32_t*>(out + b * 1024 + cta * 8 + c4);
                PIN(p); PIN(po);
                bar_sync<BAR_XGO, 288>();
                uint4 v[1];
                poll<0>(v, tag, p);
                float s[4] = {decf(v[0].x), decf(v[0].y), decf(v[0].z), decf(v[0].w)};
                red8(s);
                float r[4];
#pragma unroll
                for (int i = 0; i < 4; i++) r[i] = x2[i] + bfr(gb[i] * bfr(s[i]));
                st2(po, pack2(r[0], r[1]), pack2(r[2], r[3]), lane < 4);
            }
        }
        return;
    }

    const uint2 xr0 = *reinterpret_cast<const uint2*>(x_in + tid * 4);
    const uint2 xr1 = *reinterpret_cast<const uint2*>(x_in + 1024 + tid * 4);
    const uint2 cr0 = *reinterpret_cast<const uint2*>(c_in + tid * 4);
    const uint2 cr1 = *reinterpret_cast<const uint2*>(c_in + 1024 + tid * 4);
    const uint32_t xw = *reinterpret_cast<const uint32_t*>(x_in + (tid >> 7) * 1024 + (cta >> 5) * 256 + (tid & 127) * 2);

    const float* st_s = reinterpret_cast<const float*>(smem + SM_ST);
    const int lj = lane >> 3, l7 = lane & 7;
    const int g8 = lane >> 2, q2 = (lane & 3) * 2;
    uint32_t taddr = sbase + SM_RING + lane * 128 + ((warp ^ l7) << 4);
    uint32_t aaddr = sbase + lane * 16;
    const uint32_t fullb = sbase + SM_BAR, emptyb = sbase + SM_BAR + NSTAGE * 8;
    const uint32_t lt8 = lane < 8;
    uint32_t* pub = mine + (g8 & 1) * 64 + warp * 8 + q2;
    PIN32(taddr); PIN32(aaddr); PIN(pub);
    uint32_t* px = scr + ((cta & 3) * 32 + warp) * RSZ + R_X + (cta >> 2) * 16 + (g8 & 1) * 8 + q2;
    uint32_t* pcx = scr + (C_X + (cta & 3)) * RSZ + R_CNT + lane;
    uint32_t* py = scr + ((cta & 15) * 8 + warp) * RSZ + R_Y + (cta >> 4) * 16 + (g8 & 1) * 8 + q2;
    const int ljp = ((lj & 1) << 1) | (lj >> 1);

    uint32_t af[8][4];
    uint32_t wf[5][4][4];
    Acc acc, acc2;
    float ln0 = 0.f, ln1 = 0.f;
    uint32_t scb[2][4];

    {
    const uint32_t lo8 = lt8;
    uint32_t lane0 = lane == 0;
    PIN32(lane0);
    const uint32_t tag = 1 + (epoch & 1);
    uint32_t rdy = 0;

    auto load_af = [&](int i, int off) { lds128(af[i], aaddr + off); };
    auto load_af8 = [&](int i, uint32_t addr) {
#pragma unroll
        for (int c = 0; c < 4; c++) ldsm4(af[i + c], addr + c * 64);
    };
    auto slot = [](int it) { return it >= T_F ? it - T_F : it >= T_E ? (it - T_E) % 5 : it >= T_WO ? it - T_WO : it & 1; };
    auto tscan = [&](int it0, int n) {
        const int it = it0 + lane;
        const uint32_t m = __ballot_sync(0xffffffffu, mbar_test_p(fullb + (it % NSTAGE) * 8, (it / NSTAGE) & 1, lane < n));
        rdy = (m << (it0 & 31)) | (m >> ((32 - it0) & 31));
    };
    auto tfetch = [&](int it) {
        if (UNLIKELY(!((rdy >> (it & 31)) & 1))) mbar_wait_slow(fullb + (it % NSTAGE) * 8, (it / NSTAGE) & 1);
        if (it >= T_K && it < T_V) {
            const uint32_t ka = sbase + SM_RING + (it % NSTAGE) * STAGE_BYTES + (warp * 8 + l7) * 128;
#pragma unroll
            for (int c = 0; c < 4; c++) ldsm4(wf[slot(it)][c], ka + (c >> 1) * 8192 + ((((c & 1) * 4 + lj) ^ l7) << 4));
        } else {
#pragma unroll
            for (int c = 0; c < 4; c++) ldsm4t(wf[slot(it)][c], taddr + (it % NSTAGE) * STAGE_BYTES + c * 4096);
        }
    };
    auto tld = [&](int it) {
#pragma unroll
        for (int c = 0; c < 4; c++) ldsm4t(wf[slot(it)][c], taddr + (it % NSTAGE) * STAGE_BYTES + c * 4096);
    };
    auto tpre = [&](int it0, int n) {
        tscan(it0, n == 5 ? 7 : n);
#pragma unroll
        for (int j = 0; j < 5; j++)
            if (j < n && ((rdy >> ((it0 + j) & 31)) & 1)) tld(it0 + j);
    };
    auto tlate = [&](int it) {
        if (UNLIKELY(!((rdy >> (it & 31)) & 1))) {
            mbar_wait_slow(fullb + (it % NSTAGE) * 8, (it / NSTAGE) & 1);
            tld(it);
        }
    };
    auto tmma = [&](Acc& ac, int ai, int it, bool first) {
        const bool rows8 = it >= T_K && it < T_WO;
#pragma unroll
        for (int kt = 0; kt < 8; kt++) {
            const uint32_t b0 = wf[slot(it)][kt >> 1][(kt & 1) * 2], b1 = wf[slot(it)][kt >> 1][(kt & 1) * 2 + 1];
            if (it >= T_F && kt == 7) {
                if (first) ac.c[7][2] = ac.c[7][3] = 0.f;
            } else if (rows8) {
                if (first && kt < 4) mma16816_z(ac.c[kt], af[ai + (kt >> 1)], b0, b1);
                else mma16816(ac.c[kt & 3], af[ai + (kt >> 1)], b0, b1);
            } else {
                if (first) mma16816_z(ac.c[kt], af[ai], b0, b1);
                else mma16816(ac.c[kt], af[ai], b0, b1);
            }
        }
        if (it + NSTAGE < NBOX) {
            __syncwarp();
            mbar_arrive_p(emptyb + (it % NSTAGE) * 8, lane0);
        }
    };
    auto publish2 = [&](float v0, float v1, uint32_t* dst) {
        v0 += __shfl_xor_sync(0xffffffffu, v0, 8);
        v1 += __shfl_xor_sync(0xffffffffu, v1, 8);
        v0 += __shfl_xor_sync(0xffffffffu, v0, 16);
        v1 += __shfl_xor_sync(0xffffffffu, v1, 16);
        st2(dst, encf(v0, tag), encf(v1, tag), lo8);
    };
    auto publish = [&](const Acc& ac, uint32_t* dst) {
        float v0, v1;
        ac.pick(lj, v0, v1);
        publish2(v0, v1, dst);
    };

    {
        const uint32_t o = sbase + SM_SC + frag_off(0, tid * 4);
        sts32_p(o, pack2(silu_x(lo16(cr0.x)), silu_x(hi16(cr0.x))), 1);
        sts32_p(o + 16, pack2(silu_x(lo16(cr0.y)), silu_x(hi16(cr0.y))), 1);
        sts32_p(o + 64, pack2(silu_x(lo16(cr1.x)), silu_x(hi16(cr1.x))), 1);
        sts32_p(o + 80, pack2(silu_x(lo16(cr1.y)), silu_x(hi16(cr1.y))), 1);
        bar_sync<0, 288>();
        load_af(0, SM_SC + (cta >> 5) * 1024);
        load_af(1, SM_SC + (cta >> 5) * 1024 + 512);
        tfetch(T_A); tmma(acc, 0, T_A, true);
        tfetch(T_A + 1); tmma(acc, 1, T_A + 1, false);
        bar_sync<BAR_ZERO, 288>();
        publish(acc, pub + R_A);
        {
            const float xv[2][4] = {{lo16(xr0.x), hi16(xr0.x), lo16(xr0.y), hi16(xr0.y)},
                                    {lo16(xr1.x), hi16(xr1.x), lo16(xr1.y), hi16(xr1.y)}};
            float mb[2], den[2];
            ln_stats(xv, sbase + SM_ST, st_s, warp, lane0, mb, den);
            const float m = (tid >> 7) ? mb[1] : mb[0], dn = (tid >> 7) ? den[1] : den[0];
            ln0 = bfr(bfr(lo16(xw) - m) / dn);
            ln1 = bfr(bfr(hi16(xw) - m) / dn);
        }
    }
    {
        {
            const int b = tid >> 7, pr = tid & 127;
            const uint32_t* p = scr + ((cta >> 5) * 4 + (pr >> 5)) * RSZ + R_A + b * 64 + (pr & 31) * 2;
            uint32_t sa = sbase + SM_H + frag_off(b, pr * 2);
            PIN(p); PIN32(sa);
            uint2 v[8];
            gather<16 * RSZ>(v, tag, p);
            float sa0 = bfr((decf(v[0].x) + decf(v[2].x)) + (decf(v[4].x) + decf(v[6].x)));
            float sa1 = bfr((decf(v[0].y) + decf(v[2].y)) + (decf(v[4].y) + decf(v[6].y)));
            float ca0 = bfr((decf(v[1].x) + decf(v[3].x)) + (decf(v[5].x) + decf(v[7].x)));
            float ca1 = bfr((decf(v[1].y) + decf(v[3].y)) + (decf(v[5].y) + decf(v[7].y)));
            float h0 = bfr(ln0 * bfr(1.f + ca0)) + sa0, h1 = bfr(ln1 * bfr(1.f + ca1)) + sa1;
            sts32_p(sa, pack2(h0, h1), 1);
            tscan(T_Q, 8);
            cbar();
        }
        load_af(0, SM_H);
        load_af(1, SM_H + 512);
        tfetch(T_Q);
        tfetch(T_Q + 1); tmma(acc, 0, T_Q, true);
        tfetch(T_Q + 2); tmma(acc2, 0, T_Q + 1, true);
        tmma(acc, 1, T_Q + 2, false);
        tfetch(T_Q + 3);
        publish(acc, pub + R_Q);
        tmma(acc2, 1, T_Q + 3, false);
        publish(acc2, pub + R_Q + 128);
#pragma unroll
        for (int j = 0; j < 4; j++) load_af(j, SM_SC + (cta >> 6) * 2048 + j * 512);
#pragma unroll
        for (int j = 0; j < 4; j++) { tfetch(T_M + j); tmma(acc, j, T_M + j, j == 0); }
        publish(acc, pub + R_M);
        bar_arrive<BAR_MGO, 288>();
    }
    {
        {
            const uint32_t* p = scr + (((cta >> 4) & 3) * 8 + warp) * RSZ + R_Q + (lane >> 4) * 128 + (cta >> 6) * 64 + (lane & 15) * 4;
            uint4 v[4];
            gather<32 * RSZ>(v, tag, p);
            float q0 = (decf(v[0].x) + decf(v[1].x)) + (decf(v[2].x) + decf(v[3].x));
            float q1 = (decf(v[0].y) + decf(v[1].y)) + (decf(v[2].y) + decf(v[3].y));
            float q2f = (decf(v[0].z) + decf(v[1].z)) + (decf(v[2].z) + decf(v[3].z));
            float q3 = (decf(v[0].w) + decf(v[1].w)) + (decf(v[2].w) + decf(v[3].w));
            sts64_p(sbase + SM_Q + warp * 272 + lane * 8, pack2(q0, q1), pack2(q2f, q3), 1);
            tscan(T_K, 4);
            cbar();
        }
        float s[4][2];
        load_af8(0, sbase + SM_Q + l7 * 272 + ljp * 16);
#pragma unroll
        for (int j = 0; j < 4; j++) {
            const float scale = 0.08838834764831845f;
            tfetch(T_K + j);
            tmma(acc, 0, T_K + j, true);
            s[j][0] = bfr(bfr(acc.s0()) * scale);
            s[j][1] = bfr(bfr(acc.s1()) * scale);
        }
        const uint32_t q0lane = (lane & 3) == 0;
        float m = fmaxf(fmaxf(fmaxf(s[0][0], s[0][1]), fmaxf(s[1][0], s[1][1])), fmaxf(fmaxf(s[2][0], s[2][1]), fmaxf(s[3][0], s[3][1])));
        m = fmaxf(m, __shfl_xor_sync(0xffffffffu, m, 1));
        m = fmaxf(m, __shfl_xor_sync(0xffffffffu, m, 2));
        sts32_p(sbase + SM_ST + (64 + g8 * 8 + warp) * 4, __float_as_uint(m), q0lane);
        cbar();
        {
            const float4 a = *reinterpret_cast<const float4*>(st_s + 64 + g8 * 8);
            const float4 b = *reinterpret_cast<const float4*>(st_s + 64 + g8 * 8 + 4);
            m = fmaxf(fmaxf(fmaxf(a.x, a.y), fmaxf(a.z, a.w)), fmaxf(fmaxf(b.x, b.y), fmaxf(b.z, b.w)));
        }
        float l = 0.f;
#pragma unroll
        for (int j = 0; j < 4; j++) {
            const float p0 = __expf(s[j][0] - m), p1 = __expf(s[j][1] - m);
            l += p0 + p1;
            sts32_p(sbase + SM_P + g8 * 528 + (j * 64 + warp * 8 + q2) * 2, pack2(p0, p1), 1);
        }
        l += __shfl_xor_sync(0xffffffffu, l, 1);
        l += __shfl_xor_sync(0xffffffffu, l, 2);
        sts32_p(sbase + SM_ST + (128 + g8 * 8 + warp) * 4, __float_as_uint(l), q0lane);
        tscan(T_V, 4);
        cbar();
        {
            const float4 a = *reinterpret_cast<const float4*>(st_s + 128 + g8 * 8);
            const float4 b = *reinterpret_cast<const float4*>(st_s + 128 + g8 * 8 + 4);
            st2(mine + R_ML + g8 * 2, encf(m, tag), encf(((a.x + a.y) + (a.z + a.w)) + ((b.x + b.y) + (b.z + b.w)), tag),
                warp == 0 && q0lane);
        }
        bar_arrive<BAR_MGO, 288>();
    }
    {
        load_af8(0, sbase + SM_P + l7 * 528 + ljp * 16);
        load_af8(4, sbase + SM_P + l7 * 528 + ljp * 16 + 256);
        uint32_t* po = mine + R_O + g8 * 128 + warp * 8 + q2;
        uint32_t* pc = scr + (C_O + ((cta >> 4) & 3)) * RSZ + R_CNT + lane;
        PIN(po); PIN(pc);
        tfetch(T_V); tmma(acc, 0, T_V, true);
        tfetch(T_V + 1); tmma(acc2, 0, T_V + 1, true);
        {
            ulonglong2 w[4];
            gatherf<4>(w, tag, [&](int i) { return scr + G_SC + tid * 8 + (i >> 1) * 2048 + (i & 1) * 4; }, []() {});
#pragma unroll
            for (int i = 0; i < 4; i++) {
                scb[i >> 1][(i & 1) * 2] = (uint32_t)(w[i].x >> 32);
                scb[i >> 1][(i & 1) * 2 + 1] = (uint32_t)(w[i].y >> 32);
            }
        }
        tfetch(T_V + 2); tmma(acc, 4, T_V + 2, false);
        st2(po, encf(acc.s0(), tag), encf(acc.s1(), tag), 1);
        tfetch(T_V + 3); tmma(acc2, 4, T_V + 3, false);
        st2(po + 64, encf(acc2.s0(), tag), encf(acc2.s1(), tag), 1);
        cnt_add(pc, lane0);
        const int h = cta >> 2, b = tid >> 7, d = tid & 127;
        const uint32_t* p = scr + (b * 64 + (h >> 3) * 16) * RSZ + R_O + (h & 7) * 128 + d;
        uint32_t so = sbase + SM_H + frag_off(b, d & ~1) + (d & 1) * 2;
        PIN(p); PIN32(so); PIN(px); PIN(pcx);
        if (warp == 3) cnt_wait(scr + (C_O + (h >> 3)) * RSZ + R_CNT, 32 * 8);
        bar_sync<BAR_ALPHA, 288>();
        uint32_t v[16];
        gather<RSZ>(v, tag, p, [&]() { tpre(T_WO, 4); });
        float r[4];
#pragma unroll
        for (int j = 0; j < 4; j++) {
            const float4 a = *reinterpret_cast<const float4*>(st_s + 192 + b * 16 + j * 4);
            r[j] = (a.x * decf(v[4 * j]) + a.y * decf(v[4 * j + 1])) + (a.z * decf(v[4 * j + 2]) + a.w * decf(v[4 * j + 3]));
        }
        sts16_p(so, pack2((r[0] + r[1]) + (r[2] + r[3]), 0.f), 1);
        cbar();
    }
    {
        load_af(0, SM_H);
        tlate(T_WO); tmma(acc, 0, T_WO, true);
        tlate(T_WO + 1); tmma(acc2, 0, T_WO + 1, true);
        publish(acc, px);
        tlate(T_WO + 2); tmma(acc, 0, T_WO + 2, true);
        publish(acc2, px + 8 * RSZ);
        publish(acc, px + 16 * RSZ);
        tlate(T_WO + 3); tmma(acc2, 0, T_WO + 3, true);
        publish(acc2, px + 24 * RSZ);
        cnt_add(pcx, lane0);
    }
    {
        const uint32_t* p = scr + G_X2 + (cta % X2_COPIES) * 2048 + tid * 4;
        uint32_t so = sbase + SM_H2 + frag_off(0, tid * 4);
        PIN(p); PIN32(so);
        if (warp == 5) cnt_wait(scr + (C_X2 + (cta % X2_COPIES)) * RSZ + R_CNT, 128);
        cbar();
        uint4 v[2];
        gather<1024>(v, tag, p, [&]() { tpre(T_E, 5); });
        const float xv[2][4] = {{hi16(v[0].x), hi16(v[0].y), hi16(v[0].z), hi16(v[0].w)},
                                {hi16(v[1].x), hi16(v[1].y), hi16(v[1].z), hi16(v[1].w)}};
        float mb[2], den[2];
        ln_stats(xv, sbase + SM_ST, st_s, warp, lane0, mb, den);
#pragma unroll
        for (int b = 0; b < 2; b++) {
            float h[4];
#pragma unroll
            for (int i = 0; i < 4; i++) {
                h[i] = bfr(bfr(__fdividef(bfr(xv[b][i] - mb[b]), den[b])) * hi16(scb[b][i])) + lo16(scb[b][i]);
            }
            sts32_p(so + b * 64, pack2(h[0], h[1]), 1);
            sts32_p(so + b * 64 + 16, pack2(h[2], h[3]), 1);
        }
        cbar();
    }
    {
        const int r0 = (cta * 7) & 7, n0 = 8 - r0;
        float ga0 = 0.f, ga1 = 0.f, gb0 = 0.f, gb1 = 0.f;
        uint32_t* pch = scr + (C_H + ((cta & 63) >> 3)) * RSZ + R_CNT + lane;
        PIN(pch);
#pragma unroll
        for (int j = 0; j < 7; j++) load_af(j, SM_H2 + ((r0 + j) & 7) * 512);
#pragma unroll
        for (int j = 0; j < 7; j++) {
            if (j < 5) tlate(T_E + j);
            if (j == 6) tfetch(T_E + 6);
            tmma(acc, j, T_E + j, true);
            if (j == 3) tfetch(T_E + 5);
            float t0, t1;
            acc.pick(lj, t0, t1);
            const bool f = j < n0;
            ga0 += f ? t0 : 0.f; ga1 += f ? t1 : 0.f;
            gb0 += f ? 0.f : t0; gb1 += f ? 0.f : t1;
        }
        publish2(ga0, ga1, pub + R_H);
        publish2(gb0, gb1, pub + R_H + 128);
        cnt_add(pch, lane0);
    }
    {
        {
            const int wq = warp < 7 ? warp : 6;
            const int b = (lane >> 4) & 1, q4 = (lane & 15) * 4;
            const int pg = (cta >> 4) * 8 + wq;
            const uint32_t* p0 = scr + pg * RSZ + R_H + (wq == 0 ? 0 : 128) + b * 64 + q4;
            const uint32_t* p1 = scr + (pg + 1) * RSZ + R_H + b * 64 + q4;
            const int k = wq * 64 + q4, kb = k / 112, kk = k - kb * 112;
            uint32_t so = sbase + SM_HH + kb * 512 + frag_off(b, kk);
            PIN(p0); PIN(p1); PIN32(so); PIN(py);
            if (warp == 7) cnt_wait(scr + (C_H + (cta >> 4)) * RSZ + R_CNT, 16 * 8);
            cbar();
            uint4 v[4];
            gatherf<4>(v, tag, [&](int i) { return ((i & 1) ? p1 : p0) + (i >> 1) * 64 * RSZ; }, [&]() { tpre(T_F, 4); });
            float g[4] = {decf(v[0].x) + decf(v[1].x), decf(v[0].y) + decf(v[1].y), decf(v[0].z) + decf(v[1].z),
                          decf(v[0].w) + decf(v[1].w)};
            float u[4] = {decf(v[2].x) + decf(v[3].x), decf(v[2].y) + decf(v[3].y), decf(v[2].z) + decf(v[3].z),
                          decf(v[2].w) + decf(v[3].w)};
            float r[4];
#pragma unroll
            for (int i = 0; i < 4; i++) r[i] = bfr(silu_f(bfr(g[i]))) * bfr(u[i]);
            sts32_p(so, pack2(r[0], r[1]), 1);
            sts32_p(so + 16, pack2(r[2], r[3]), 1);
            cbar();
        }
#pragma unroll
        for (int j = 0; j < 4; j++) load_af(j, SM_HH + j * 512);
        bar_arrive<BAR_XGO, 288>();
#pragma unroll
        for (int j = 0; j < 4; j++) { tlate(T_F + j); tmma(acc, j, T_F + j, j == 0); }
        publish(acc, py);
    }
    }
}

typedef CUresult (*EncodeFn)(CUtensorMap*, CUtensorMapDataType, cuuint32_t, void*, const cuuint64_t*,
                             const cuuint64_t*, const cuuint32_t*, const cuuint32_t*, CUtensorMapInterleave,
                             CUtensorMapSwizzle, CUtensorMapL2promotion, CUtensorMapFloatOOBfill);

void make_map(EncodeFn fn, CUtensorMap* m, const void* base, uint64_t rows, uint64_t cols, uint32_t box_rows) {
    cuuint64_t gd[3] = {cols, rows, 1};
    cuuint64_t gs[2] = {cols * 2, cols * 2 * rows};
    cuuint32_t bx[3] = {64, box_rows, 1};
    cuuint32_t es[3] = {1, 1, 1};
    fn(m, CU_TENSOR_MAP_DATA_TYPE_BFLOAT16, 3, const_cast<void*>(base), gd, gs, bx, es,
       CU_TENSOR_MAP_INTERLEAVE_NONE, CU_TENSOR_MAP_SWIZZLE_128B, CU_TENSOR_MAP_L2_PROMOTION_L2_128B, CU_TENSOR_MAP_FLOAT_OOB_FILL_NONE);
}
void make_map_k(EncodeFn fn, CUtensorMap* m, const void* base, uint64_t rows) {
    cuuint64_t gd[3] = {64, rows, 2};
    cuuint64_t gs[2] = {256, 128};
    cuuint32_t bx[3] = {64, 64, 2};
    cuuint32_t es[3] = {1, 1, 1};
    fn(m, CU_TENSOR_MAP_DATA_TYPE_BFLOAT16, 3, const_cast<void*>(base), gd, gs, bx, es,
       CU_TENSOR_MAP_INTERLEAVE_NONE, CU_TENSOR_MAP_SWIZZLE_128B, CU_TENSOR_MAP_L2_PROMOTION_L2_128B, CU_TENSOR_MAP_FLOAT_OOB_FILL_NONE);
}

}

extern "C" void kernel_launch(void* const* d_in, const int* in_sizes, int n_in, void* d_out, int out_size) {
    (void)in_sizes; (void)n_in; (void)out_size;
    static EncodeFn enc_fn = nullptr;
    if (!enc_fn) {
        cudaDriverEntryPointQueryResult qr;
        void* fn = nullptr;
        cudaGetDriverEntryPoint("cuTensorMapEncodeTiled", &fn, cudaEnableDefault, &qr);
        enc_fn = (EncodeFn)fn;
        cudaFuncSetAttribute(fused_kernel, cudaFuncAttributeMaxDynamicSharedMemorySize, SM_TOTAL);
    }
    Maps maps;
    make_map(enc_fn, &maps.mod, d_in[10], 1024, 6144, 128);
    make_map(enc_fn, &maps.wq, d_in[3], 1024, 4096, 128);
    make_map_k(enc_fn, &maps.k, d_in[1], (uint64_t)8 * SK);
    make_map(enc_fn, &maps.v, d_in[2], (uint64_t)8 * SK, 128, 128);
    make_map(enc_fn, &maps.wo, d_in[4], 4096, 1024, 128);
    make_map(enc_fn, &maps.w1, d_in[6], 1024, 3584, 128);
    make_map(enc_fn, &maps.w3, d_in[7], 1024, 3584, 128);
    make_map(enc_fn, &maps.w2, d_in[8], 3584, 1024, 112);
    fused_kernel<<<NCTA, NTHREADS, SM_TOTAL>>>(maps, (const __nv_bfloat16*)d_in[0], (const __nv_bfloat16*)d_in[9],
                                               (__nv_bfloat16*)d_out);
}
```
